```python
import torch

def _softmax(x, axis=-1):
    return torch.softmax(x, dim=axis)
def _gelu(x):
    return torch.nn.functional.gelu(x, approximate="tanh")
def _silu(x):
    return torch.nn.functional.silu(x)
def _sigmoid(x):
    return torch.sigmoid(x)
def _layernorm(x, axis=-1, eps=1e-5):
    m = x.mean(dim=axis, keepdim=True)
    v = x.var(dim=axis, keepdim=True, unbiased=False)
    return (x - m) / torch.sqrt(v + eps)
def _scatter_add(tgt, idx, src, axis=0):
    return tgt.clone().index_add_(axis, idx, src)
def _segment_sum(src, seg, n):
    out = torch.zeros((n,) + src.shape[1:], dtype=src.dtype)
    return out.index_add_(0, seg, src)
def _pad(x, pw):
    flat = tuple(v for pair in reversed(pw) for v in pair)
    return torch.nn.functional.pad(x, flat)

kernel_name = 'parallel_sum__mha_block_cached__dense_activation_gelu__decode'

def setup_inputs():

    _w = (lambda a: (lambda t: t.to(torch.bfloat16) if t.is_floating_point() else t)(torch.as_tensor(a)))
    def _A_setup():
        B, Sq, D = 8, 1, 512
        H, Sk, Dh = 32, 4096, 128
        return {
            "x": _w((lambda *s: torch.randn(*s, dtype=torch.bfloat16) * 0.05)(B, Sq, D)),
            "k_cache": _w((lambda *s: torch.randn(*s, dtype=torch.bfloat16) * 3.2)(B, H, Sk, Dh)),
            "v_cache": _w((lambda *s: torch.randn(*s, dtype=torch.bfloat16) * 0.8)(B, H, Sk, Dh)),
            "wq": _w((lambda *s: torch.randn(*s, dtype=torch.bfloat16) * 3.2)(D, H * Dh) * (D ** -0.5)),
            "wo": _w((lambda *s: torch.randn(*s, dtype=torch.bfloat16) * 0.8)(H * Dh, D) * ((H * Dh) ** -0.5)),
        }
    _A_in = _A_setup()

    def _B_setup():
        B, S, D, F = 8, 1, 512, 1792
        return {
            "x": _w((lambda *s: torch.randn(*s, dtype=torch.bfloat16) * 0.05)(B, S, D)),
            "w1": _w((lambda *s: torch.randn(*s, dtype=torch.bfloat16) * 3.2)(D, F) * (D ** -0.5)),
            "b1": _w((lambda *s: torch.randn(*s, dtype=torch.bfloat16) * 3.2)(F) * 0.01),
            "w2": _w((lambda *s: torch.randn(*s, dtype=torch.bfloat16) * 0.4)(F, D) * (F ** -0.5)),
            "b2": _w((lambda *s: torch.randn(*s, dtype=torch.bfloat16) * 0.4)(D) * 0.01),
        }
    _B_in = _B_setup()

    return {
        "A_x": _A_in["x"],
        "A_k_cache": _A_in["k_cache"],
        "A_v_cache": _A_in["v_cache"],
        "A_wq": _A_in["wq"],
        "A_wo": _A_in["wo"],
        "B_x": _B_in["x"],
        "B_w1": _B_in["w1"],
        "B_b1": _B_in["b1"],
        "B_w2": _B_in["w2"],
        "B_b2": _B_in["b2"],
    }

def reference(A_x, A_k_cache, A_v_cache, A_wq, A_wo, B_x, B_w1, B_b1, B_w2, B_b2):
    def _A_ref(x, k_cache, v_cache, wq, wo):
        B, Sq, D = x.shape
        H, Dh = 32, 128
        q = (lambda x, *d: x.permute(*d))((x @ wq).reshape(B, Sq, H, Dh), 0, 2, 1, 3)
        scores = torch.einsum("bhqd,bhkd->bhqk", q, k_cache) * (Dh ** -0.5)
        p = _softmax(scores, axis=-1)
        o = torch.einsum("bhqk,bhkd->bhqd", p, v_cache)
        return (lambda x, *d: x.permute(*d))(o, 0, 2, 1, 3).reshape(B, Sq, H * Dh) @ wo

    def _B_ref(x, w1, b1, w2, b2):
        h = torch.einsum("bsd,df->bsf", x, w1) + b1
        h = _gelu(h)
        return torch.einsum("bsf,fd->bsd", h, w2) + b2

    x = A_x
    xn = _layernorm(x, axis=-1)
    return x + _A_ref(xn, A_k_cache, A_v_cache, A_wq, A_wo) + _B_ref(xn, B_w1, B_b1, B_w2, B_b2)
```

```cpp
#include <cuda_runtime.h>
#include <cuda.h>
#include <cuda_bf16.h>
#include <stdint.h>

namespace {

constexpr int NB = 8, NH = 32, SK = 4096, DH = 128, DM = 512, FF = 1792;
constexpr int NPAIR = NB * NH;

#define CFG_NSLOT 6
#define CFG_LAG 32
#define CFG_NU 4
#define CFG_W 2
#define CFG_TICKET_HF 1
#define CFG_TR 1
#define CFG_TAILFREE 0
#define CFG_ALL_EF 0
#define CFG_QH 8
constexpr int HG = 4;
constexpr int LAG = CFG_LAG;
constexpr int NSLOT = CFG_NSLOT;
constexpr int NU = CFG_NU;
constexpr int NSPEC = 4 * NU;
constexpr int ITEM_KEYS = 128;
constexpr int ITEM_BYTES = ITEM_KEYS * DH * 2;
constexpr int IPP = SK / ITEM_KEYS;
constexpr int SPP = IPP / 2;
constexpr int TOTAL_SUPER = NPAIR * SPP * 2;
constexpr int WINF = CFG_W;
constexpr int TR_GROUPS = CFG_TR;
constexpr int TAIL_FREE = CFG_TAILFREE;
constexpr int QH_STREAM = CFG_QH;
constexpr int NTHREADS = (8 + 1 + NSLOT) * 32;
constexpr int MAX_CTAS = 256;

constexpr int XN_PITCH = 1040;
constexpr int S_RING = 0;
constexpr int S_QP = S_RING + NSLOT * ITEM_BYTES;
constexpr int S_RED = S_QP + NSLOT * 256;
constexpr int PRO_BYTES = 8 * XN_PITCH + 8 * 8 * 20 * 4;
constexpr int RED_BYTES = (NSLOT * 4096 > PRO_BYTES) ? NSLOT * 4096 : PRO_BYTES;
constexpr int S_BAR = S_RED + RED_BYTES;
constexpr int S_PBAR = S_BAR + 4 * NSLOT * 8;
constexpr int S_DESC = S_PBAR + 16;
constexpr int S_EPOCH = S_DESC + NSLOT * 4;
constexpr int STREAM_SMEM = S_EPOCH + 16;

constexpr int CH_BYTES = 128 * 128 * 2;
constexpr int NBUF = 5;
constexpr int H_PITCH = FF * 2 + 16;
constexpr int P_RING = 0;
constexpr int P_XN = P_RING + NBUF * CH_BYTES;
constexpr int P_H = P_XN + 8 * XN_PITCH;
constexpr int P_O = P_H + 8 * H_PITCH;
constexpr int P_ZERO = P_O + HG * 2 * 256;
constexpr int P_BAR = P_ZERO + 256;
constexpr int P_END = P_BAR + (NBUF + HG + 4 * HG) * 8;
constexpr int SMEM_BYTES = (STREAM_SMEM > P_END + 16) ? STREAM_SMEM : P_END + 16;
constexpr int EPOCH_OFF = SMEM_BYTES - 16;
static_assert(SMEM_BYTES <= 232448, "smem");
static_assert(9 + NSLOT >= 9 + HG, "warps");
static_assert(NSLOT >= 3 && WINF >= 2 && WINF <= NSLOT, "ring");
static_assert(S_EPOCH <= EPOCH_OFF, "smem");

constexpr long long SPIN_LIMIT = 2000000000LL;

__device__ unsigned int g_epoch[MAX_CTAS];
__device__ unsigned int g_ticket;
__device__ __align__(128) uint32_t g_q[NPAIR * DH];
__device__ __align__(128) uint32_t g_sc[NPAIR * SK];
__device__ __align__(128) unsigned long long g_st[NPAIR * IPP];
__device__ __align__(128) uint32_t g_op[NPAIR * SPP * DH];
__device__ __align__(128) uint32_t g_h[NB * FF];

#define TS(i) do {} while (0)

__device__ __forceinline__ uint32_t smem_u32(const void* p) { return (uint32_t)__cvta_generic_to_shared(p); }
__device__ __forceinline__ float bf16r(float x) { return __bfloat162float(__float2bfloat16_rn(x)); }
__device__ __forceinline__ float bflo(uint32_t w) { return __uint_as_float(w << 16); }
__device__ __forceinline__ float bfhi(uint32_t w) { return __uint_as_float(w & 0xFFFF0000u); }
__device__ __forceinline__ uint32_t pack2(float lo, float hi) {
    uint32_t r;
    asm("cvt.rn.bf16x2.f32 %0, %1, %2;" : "=r"(r) : "f"(hi), "f"(lo));
    return r;
}
__device__ __forceinline__ void mbar_init(uint32_t bar, int cnt) {
    asm volatile("mbarrier.init.shared::cta.b64 [%0], %1;" ::"r"(bar), "r"(cnt) : "memory");
}
__device__ __forceinline__ void mbar_expect_tx(uint32_t bar, uint32_t bytes) {
    asm volatile("mbarrier.arrive.expect_tx.shared::cta.b64 _, [%0], %1;" ::"r"(bar), "r"(bytes) : "memory");
}
__device__ __forceinline__ void mbar_arrive(uint32_t bar) {
    asm volatile("mbarrier.arrive.shared::cta.b64 _, [%0];" ::"r"(bar) : "memory");
}
__device__ __forceinline__ bool mbar_try(uint32_t bar, uint32_t parity) {
    uint32_t ok;
    asm volatile(
        "{\n.reg .pred p;\nmbarrier.try_wait.parity.shared::cta.b64 p, [%1], %2;\nselp.u32 %0, 1, 0, p;\n}"
        : "=r"(ok) : "r"(bar), "r"(parity) : "memory");
    return ok != 0;
}
__device__ __forceinline__ void mbar_wait(uint32_t bar, uint32_t parity) {
    if (mbar_try(bar, parity)) return;
    long long t0 = clock64();
    while (!mbar_try(bar, parity)) {
        if (clock64() - t0 > SPIN_LIMIT) __trap();
    }
}
__device__ __forceinline__ void bulk_load(uint32_t dst, const void* src, uint32_t bytes, uint32_t bar, uint64_t pol) {
    asm volatile(
        "cp.async.bulk.shared::cluster.global.mbarrier::complete_tx::bytes.L2::cache_hint [%0], [%1], %2, [%3], %4;"
        ::"r"(dst), "l"(src), "r"(bytes), "r"(bar), "l"(pol) : "memory");
}
__device__ __forceinline__ void bar_sync256() { asm volatile("bar.sync 1, 256;" ::: "memory"); }

__device__ __forceinline__ uint4 lds128(uint32_t a) {
    uint4 v;
    asm volatile("ld.shared.v4.u32 {%0,%1,%2,%3}, [%4];" : "=r"(v.x), "=r"(v.y), "=r"(v.z), "=r"(v.w) : "r"(a));
    return v;
}
__device__ __forceinline__ uint2 lds64(uint32_t a) {
    uint2 v;
    asm volatile("ld.shared.v2.u32 {%0,%1}, [%2];" : "=r"(v.x), "=r"(v.y) : "r"(a));
    return v;
}
__device__ __forceinline__ uint32_t lds32(uint32_t a) {
    uint32_t v;
    asm volatile("ld.shared.u32 %0, [%1];" : "=r"(v) : "r"(a));
    return v;
}
__device__ __forceinline__ void sts128(uint32_t a, uint32_t x, uint32_t y, uint32_t z, uint32_t w) {
    asm volatile("st.shared.v4.u32 [%0], {%1,%2,%3,%4};" ::"r"(a), "r"(x), "r"(y), "r"(z), "r"(w) : "memory");
}
__device__ __forceinline__ void sts64(uint32_t a, uint32_t x, uint32_t y) {
    asm volatile("st.shared.v2.u32 [%0], {%1,%2};" ::"r"(a), "r"(x), "r"(y) : "memory");
}
__device__ __forceinline__ void sts32(uint32_t a, uint32_t x) {
    asm volatile("st.shared.u32 [%0], %1;" ::"r"(a), "r"(x) : "memory");
}
__device__ __forceinline__ void sts16(uint32_t a, uint32_t x) {
    asm volatile("st.shared.u16 [%0], %1;" ::"r"(a), "h"((unsigned short)x) : "memory");
}
__device__ __forceinline__ void ldsm4t(uint32_t a, uint32_t& r0, uint32_t& r1, uint32_t& r2, uint32_t& r3) {
    asm volatile("ldmatrix.sync.aligned.m8n8.x4.trans.shared.b16 {%0,%1,%2,%3}, [%4];"
                 : "=r"(r0), "=r"(r1), "=r"(r2), "=r"(r3) : "r"(a));
}
__device__ __forceinline__ void ldsm4(uint32_t a, uint32_t& r0, uint32_t& r1, uint32_t& r2, uint32_t& r3) {
    asm volatile("ldmatrix.sync.aligned.m8n8.x4.shared.b16 {%0,%1,%2,%3}, [%4];"
                 : "=r"(r0), "=r"(r1), "=r"(r2), "=r"(r3) : "r"(a));
}
__device__ __forceinline__ void mma16816(float* c, uint32_t a0, uint32_t a1, uint32_t a2, uint32_t a3, uint32_t b0, uint32_t b1) {
    asm volatile(
        "mma.sync.aligned.m16n8k16.row.col.f32.bf16.bf16.f32 {%0,%1,%2,%3}, {%4,%5,%6,%7}, {%8,%9}, {%0,%1,%2,%3};"
        : "+f"(c[0]), "+f"(c[1]), "+f"(c[2]), "+f"(c[3])
        : "r"(a0), "r"(a1), "r"(a2), "r"(a3), "r"(b0), "r"(b1));
}
__device__ __forceinline__ uint4 ldx128(const void* p) {
    uint4 v;
    asm volatile("ld.relaxed.gpu.global.v4.u32 {%0,%1,%2,%3}, [%4];" : "=r"(v.x), "=r"(v.y), "=r"(v.z), "=r"(v.w) : "l"(p) : "memory");
    return v;
}
__device__ __forceinline__ unsigned long long ldx64(const void* p) {
    unsigned long long v;
    asm volatile("ld.relaxed.gpu.global.u64 %0, [%1];" : "=l"(v) : "l"(p) : "memory");
    return v;
}
__device__ __forceinline__ void stx128(void* p, uint32_t x, uint32_t y, uint32_t z, uint32_t w) {
    asm volatile("st.relaxed.gpu.global.v4.u32 [%0], {%1,%2,%3,%4};" ::"l"(p), "r"(x), "r"(y), "r"(z), "r"(w) : "memory");
}
__device__ __forceinline__ void stx64(void* p, unsigned long long v) {
    asm volatile("st.relaxed.gpu.global.u64 [%0], %1;" ::"l"(p), "l"(v) : "memory");
}
__device__ __forceinline__ void stx32(void* p, uint32_t v) {
    asm volatile("st.relaxed.gpu.global.u32 [%0], %1;" ::"l"(p), "r"(v) : "memory");
}
__device__ __forceinline__ uint4 ldg128(const void* p) {
    uint4 v;
    asm volatile("ld.global.nc.L1::no_allocate.v4.u32 {%0,%1,%2,%3}, [%4];" : "=r"(v.x), "=r"(v.y), "=r"(v.z), "=r"(v.w) : "l"(p));
    return v;
}
__device__ __forceinline__ uint2 ldg64(const void* p) {
    uint2 v;
    asm volatile("ld.global.nc.L1::no_allocate.v2.u32 {%0,%1}, [%2];" : "=r"(v.x), "=r"(v.y) : "l"(p));
    return v;
}
__device__ __forceinline__ uint32_t ldg32(const void* p) {
    uint32_t v;
    asm volatile("ld.global.nc.L1::no_allocate.u32 %0, [%1];" : "=r"(v) : "l"(p));
    return v;
}
__device__ __forceinline__ float ldg_bf16(const __nv_bfloat16* p) { return __bfloat162float(__ldg(p)); }
__device__ __forceinline__ void cp_async16(uint32_t dst, const void* src) {
    asm volatile("cp.async.cg.shared.global [%0], [%1], 16;" ::"r"(dst), "l"(src) : "memory");
}
__device__ __forceinline__ void cp_commit() { asm volatile("cp.async.commit_group;" ::: "memory"); }
template <int N>
__device__ __forceinline__ void cp_wait() { asm volatile("cp.async.wait_group %0;" ::"n"(N) : "memory"); }

__device__ __forceinline__ float warp_max(float v) {
#pragma unroll
    for (int o = 16; o > 0; o >>= 1) v = fmaxf(v, __shfl_xor_sync(0xffffffffu, v, o));
    return v;
}
__device__ __forceinline__ float warp_sum(float v) {
#pragma unroll
    for (int o = 16; o > 0; o >>= 1) v += __shfl_xor_sync(0xffffffffu, v, o);
    return v;
}
struct Spin {
    long long t0;
    __device__ __forceinline__ Spin() : t0(0) {}
    __device__ __forceinline__ void tick(unsigned ns) {
        if (t0 == 0) t0 = clock64();
        else if (clock64() - t0 > SPIN_LIMIT) __trap();
        if (ns) __nanosleep(ns);
    }
};

struct Params {
    CUtensorMap tm_wqs, tm_wq, tm_w1, tm_w2, tm_wo;
    const __nv_bfloat16 *x, *k, *v, *b1, *b2;
    __nv_bfloat16* out;
    int nstream;
};
__device__ __forceinline__ uint64_t policy_evict_first() {
    uint64_t pol;
    asm volatile("createpolicy.fractional.L2::evict_first.b64 %0, 1.0;" : "=l"(pol));
    return pol;
}
__device__ __forceinline__ uint64_t policy_evict_normal() {
    uint64_t pol;
    asm volatile("createpolicy.fractional.L2::evict_normal.b64 %0, 1.0;" : "=l"(pol));
    return pol;
}
__device__ __forceinline__ void tma_2d(uint32_t dst, const CUtensorMap* tm, int x, int y, uint32_t bar, uint64_t pol) {
    asm volatile("cp.async.bulk.tensor.2d.shared::cluster.global.tile.mbarrier::complete_tx::bytes.L2::cache_hint [%0], [%1, {%2, %3}], [%4], %5;"
                 ::"r"(dst), "l"(tm), "r"(x), "r"(y), "r"(bar), "l"(pol) : "memory");
}
__device__ __forceinline__ void chunk_tma(uint32_t dst, const CUtensorMap* tm, int col, int row, uint32_t bar, bool shared_by_many) {
    const uint64_t pol = (shared_by_many && !CFG_ALL_EF) ? policy_evict_normal() : policy_evict_first();
    mbar_expect_tx(bar, CH_BYTES);
    tma_2d(dst, tm, col, row, bar, pol);
    tma_2d(dst + CH_BYTES / 2, tm, col + 64, row, bar, pol);
}

__device__ __forceinline__ uint32_t decode_super(int idx) {
    constexpr int A = LAG * SPP;
    constexpr int MID = (NPAIR - LAG) * SPP * 2;
    int p, ch, is_v;
    if (idx < A) {
        is_v = 0; p = idx / SPP; ch = idx % SPP;
    } else if (idx < A + MID) {
        int j = idx - A;
        is_v = (j & 1) ^ 1;
        ch = (j >> 1) % SPP;
        p = j / (2 * SPP) + (is_v ? 0 : LAG);
    } else {
        int j = idx - A - MID;
        is_v = 1; p = NPAIR - LAG + j / SPP; ch = j % SPP;
    }
    const int grp = p / (8 * HG), r = p % (8 * HG);
    const bool tr = grp >= NH / HG - TR_GROUPS;
    const int b = tr ? r % 8 : r / HG, h = grp * HG + (tr ? r / 8 : r % HG);
    return ((uint32_t)is_v << 31) | ((uint32_t)(b * NH + h) << 8) | (uint32_t)(ch * 2);
}
constexpr uint32_t STOPD = 0x7FFFFFFFu;

__device__ __forceinline__ void layernorm_row(uint4 xa, uint4 xb, uint32_t dst_row, int lane) {
    float v[16];
    v[0] = bflo(xa.x); v[1] = bfhi(xa.x); v[2] = bflo(xa.y); v[3] = bfhi(xa.y);
    v[4] = bflo(xa.z); v[5] = bfhi(xa.z); v[6] = bflo(xa.w); v[7] = bfhi(xa.w);
    v[8] = bflo(xb.x); v[9] = bfhi(xb.x); v[10] = bflo(xb.y); v[11] = bfhi(xb.y);
    v[12] = bflo(xb.z); v[13] = bfhi(xb.z); v[14] = bflo(xb.w); v[15] = bfhi(xb.w);
    float s = 0.f;
#pragma unroll
    for (int i = 0; i < 16; i++) s += v[i];
    s = warp_sum(s);
    const float mean = s * (1.0f / DM);
    float q = 0.f;
#pragma unroll
    for (int i = 0; i < 16; i++) { float d = v[i] - mean; q += d * d; }
    q = warp_sum(q);
    const float m = bf16r(mean);
    const float var = bf16r(q * (1.0f / DM));
    const float den = bf16r(sqrtf(bf16r(var + 1e-5f)));
    uint32_t o[8];
#pragma unroll
    for (int i = 0; i < 8; i++) {
        float a = bf16r(v[2 * i] - m) / den;
        float b = bf16r(v[2 * i + 1] - m) / den;
        o[i] = pack2(a, b);
    }
    sts128(dst_row + lane * 16, o[0], o[1], o[2], o[3]);
    sts128(dst_row + 512 + lane * 16, o[4], o[5], o[6], o[7]);
}

__device__ __forceinline__ void chunk_load_a(uint32_t (&a)[8][4], uint32_t chunk, int warp, int lane) {
    const uint32_t a_addr = chunk + (warp >> 2) * (CH_BYTES / 2) + ((lane & 7) + ((lane >> 4) & 1) * 8) * 128 +
                            ((((warp & 3) * 2 + ((lane >> 3) & 1)) ^ (lane & 7)) << 4);
#pragma unroll
    for (int ks = 0; ks < 8; ks++) ldsm4t(a_addr + ks * 16 * 128, a[ks][0], a[ks][1], a[ks][2], a[ks][3]);
}
__device__ __forceinline__ void chunk_mma_b(float (&acc)[4][4], const uint32_t (&a)[8][4], uint32_t b_addr) {
    uint32_t bb[4][4];
#pragma unroll
    for (int q = 0; q < 4; q++) ldsm4(b_addr + q * 64, bb[q][0], bb[q][1], bb[q][2], bb[q][3]);
#pragma unroll
    for (int ks = 0; ks < 8; ks++)
        mma16816(acc[ks & 3], a[ks][0], a[ks][1], a[ks][2], a[ks][3], bb[ks >> 1][(ks & 1) * 2], bb[ks >> 1][(ks & 1) * 2 + 1]);
}
__device__ __forceinline__ void chunk_mma(float (&acc)[4][4], uint32_t chunk, uint32_t act, int act_pitch, int warp, int lane) {
    uint32_t a[8][4];
    chunk_load_a(a, chunk, warp, lane);
    chunk_mma_b(acc, a, act + (lane & 7) * act_pitch + (lane >> 3) * 16);
}
__device__ __forceinline__ float acc_sum(const float (&acc)[4][4], int e) { return (acc[0][e] + acc[1][e]) + (acc[2][e] + acc[3][e]); }
__device__ __forceinline__ void acc_zero(float (&acc)[4][4]) {
#pragma unroll
    for (int i = 0; i < 4; i++)
#pragma unroll
        for (int e = 0; e < 4; e++) acc[i][e] = 0.f;
}
__device__ __forceinline__ float gelu_tanh(float x) {
    const float kBeta = 0.7978845608028654f, kKappa = 0.044715f;
    float inner = kBeta * (x + kKappa * x * x * x);
    return 0.5f * x * (1.0f + tanhf(inner));
}

__device__ __forceinline__ void pair_seq(int n, int& grp, int& hl, int& bi) {
    constexpr int RPG = NB / NU;
    grp = n / (RPG * HG);
    const int q = n % (RPG * HG);
    const bool tr = grp >= NH / HG - TR_GROUPS;
    hl = tr ? q / RPG : q % HG;
    bi = tr ? q % RPG : q / HG;
}
constexpr int NPOLL = 4;
constexpr int NSEQ = NPAIR / NU;
__device__ void special_cta(const Params& P, uint32_t sb, uint32_t epoch, int sidx, int tid) {
    const int warp = tid >> 5, lane = tid & 31, g = lane >> 2, t = lane & 3;
    const int j = sidx & 3;
    const int u = sidx >> 2;
    const uint32_t tag16 = epoch & 0xFFFFu;

    const int nq = (NH - QH_STREAM - sidx + NSPEC - 1) / NSPEC;
    const int nslab = (FF / 128 - sidx + NSPEC - 1) / NSPEC;
    const int n0 = nq * 4, n1 = n0 + nslab * 4, ntot = n1 + FF / 128;
    const uint32_t pbar = sb + P_BAR;
    auto issue = [&](int i) {
        if (i < ntot) {
            const uint32_t dst = sb + P_RING + (i % NBUF) * CH_BYTES, bar = pbar + (i % NBUF) * 8;
            if (i < n0) chunk_tma(dst, &P.tm_wq, (QH_STREAM + sidx + (i >> 2) * NSPEC) * 128, (i & 3) * 128, bar, false);
            else if (i < n1) chunk_tma(dst, &P.tm_w1, (sidx + ((i - n0) >> 2) * NSPEC) * 128, (i & 3) * 128, bar, false);
            else chunk_tma(dst, &P.tm_w2, j * 128, (i - n1) * 128, bar, true);
        }
    };
    if (tid == 0) {
#pragma unroll 1
        for (int i = 0; i < NBUF - 1; i++) issue(i);
    }
    uint32_t par = 0;
    {
        uint4 xa = ldg128(P.x + warp * DM + lane * 8), xb = ldg128(P.x + warp * DM + 256 + lane * 8);
        layernorm_row(xa, xb, sb + P_XN + warp * XN_PITCH, lane);
    }
    float acc[4][4];
    acc_zero(acc);
#pragma unroll 1
    for (int i = 0; i < ntot; i++) {
        if (i == n1) {
            Spin sp;
#pragma unroll 1
            for (int c0 = tid; c0 < NB * FF / 4; c0 += 256 * 7) {
                uint4 w[7];
#pragma unroll
                for (int q = 0; q < 7; q++) w[q] = ldx128(g_h + (c0 + q * 256) * 4);
#pragma unroll
                for (int q = 0; q < 7; q++) {
                    const int c = c0 + q * 256;
                    while (((w[q].x & 0xFFFFu) != tag16) | ((w[q].y & 0xFFFFu) != tag16) | ((w[q].z & 0xFFFFu) != tag16) | ((w[q].w & 0xFFFFu) != tag16)) {
                        sp.tick(100);
                        w[q] = ldx128(g_h + c * 4);
                    }
                    int b = c / (FF / 4), col = (c % (FF / 4)) * 4;
                    sts64(sb + P_H + b * H_PITCH + col * 2, (w[q].x >> 16) | (w[q].y & 0xFFFF0000u), (w[q].z >> 16) | (w[q].w & 0xFFFF0000u));
                }
            }
        }
        bar_sync256();
        if (tid == 0) issue(i + NBUF - 1);
        const int sl = i % NBUF;
        mbar_wait(pbar + sl * 8, (par >> sl) & 1u);
        par ^= 1u << sl;
        uint32_t chunk = sb + P_RING + sl * CH_BYTES;
        if (i < n1) {
            chunk_mma(acc, chunk, sb + P_XN + (i & 3) * 256, XN_PITCH, warp, lane);
            if ((i & 3) == 3) {
                if (i < n0) {
                    const int h = QH_STREAM + sidx + (i >> 2) * NSPEC;
#pragma unroll
                    for (int e = 0; e < 4; e++) {
                        int c = warp * 16 + g + (e >> 1) * 8, b = 2 * t + (e & 1);
                        stx32(g_q + (b * NH + h) * DH + c, (__float_as_uint(bf16r(acc_sum(acc, e))) & 0xFFFF0000u) | tag16);
                    }
                } else {
                    const int col = (sidx + ((i - n0) >> 2) * NSPEC) * 128 + warp * 16 + g;
#pragma unroll
                    for (int e = 0; e < 4; e++) {
                        int c = col + (e >> 1) * 8, b = 2 * t + (e & 1);
                        float hp = bf16r(acc_sum(acc, e));
                        float hb = bf16r(hp + ldg_bf16(P.b1 + c));
                        float gl = bf16r(gelu_tanh(hb));
                        stx32(g_h + b * FF + c, (__float_as_uint(gl) & 0xFFFF0000u) | tag16);
                    }
                }
                acc_zero(acc);
            }
        } else {
            chunk_mma(acc, chunk, sb + P_H + (i - n1) * 256, H_PITCH, warp, lane);
        }
    }
    const int col0 = j * 128 + warp * 16 + g;
    float ffn[4], xin[4];
#pragma unroll
    for (int e = 0; e < 4; e++) {
        int c = col0 + (e >> 1) * 8, b = 2 * t + (e & 1);
        ffn[e] = bf16r(bf16r(acc_sum(acc, e)) + ldg_bf16(P.b2 + c));
        xin[e] = ldg_bf16(P.x + b * DM + c);
    }
    acc_zero(acc);
    if (tid == 0) TS(2);
    bar_sync256();
    if (tid == 0) {
#pragma unroll 1
        for (int c = 0; c < HG; c++) chunk_tma(sb + P_RING + c * CH_BYTES, &P.tm_wo, j * 128, c * 128, pbar + c * 8, true);
    }
    const uint32_t bar_cempty = pbar + NBUF * 8, bar_ofull = bar_cempty + HG * 8, bar_oempty = bar_ofull + 2 * HG * 8;
    constexpr int RPG = NB / NU;
#pragma unroll 1
    for (int n = 0; n < NPAIR / NU; n++) {
        int grp, hl, bi;
        pair_seq(n, grp, hl, bi);
        const int b = u + bi * NU;
        const int ob = (n % 4) * 2 + ((n >> 2) & 1);
        if (bi == 0) mbar_wait(pbar + hl * 8, ((par >> hl) ^ grp) & 1u);
        uint32_t a[8][4];
        chunk_load_a(a, sb + P_RING + hl * CH_BYTES, warp, lane);
        mbar_wait(bar_ofull + ob * 8, (n >> 3) & 1);
        const uint32_t b_addr = ((lane & 7) == b ? sb + P_O + ob * 256 : sb + P_ZERO) + (lane >> 3) * 16;
        chunk_mma_b(acc, a, b_addr);
        __syncwarp();
        if (lane == 0) {
            mbar_arrive(bar_oempty + ob * 8);
            if (bi == RPG - 1) mbar_arrive(bar_cempty + hl * 8);
        }
    }
    if (tid == 0) TS(3);
#pragma unroll
    for (int e = 0; e < 4; e++) {
        int c = col0 + (e >> 1) * 8, b = 2 * t + (e & 1);
        if (b % NU == u) {
            float a = bf16r(acc_sum(acc, e));
            float r = bf16r(bf16r(xin[e] + a) + ffn[e]);
            P.out[b * DM + c] = __float2bfloat16_rn(r);
        }
    }
    if (tid == 0) TS(4);
}

__device__ void special_poller(uint32_t sb, uint32_t epoch, int sidx, int pid, int lane) {
    const int u = sidx >> 2, g = lane >> 2, t = lane & 3;
    const uint32_t tag2 = epoch & 3u;
    const uint32_t pbar = sb + P_BAR;
    const uint32_t bar_ofull = pbar + (NBUF + HG) * 8, bar_oempty = bar_ofull + 2 * NPOLL * 8;
    constexpr int NV = SPP;
    bool waited = true;
    {
#pragma unroll 1
        for (int n = pid; n < NSEQ; n += NPOLL) {
            int grp, hl, bi;
            pair_seq(n, grp, hl, bi);
            const int b = u + bi * NU, rnd = n / NPOLL;
            const uint32_t* src = g_op + (size_t)(b * NH + grp * HG + hl) * SPP * DH + lane * 4;
            uint4 v[NV];
            uint32_t pending = 0;
            Spin sp;
            bool spun = false;
            if (waited) {
                const uint32_t* gate = src + (grp == NH / HG - 1 ? 0 : (NV - 1) * DH);
                uint4 w = ldx128(gate);
                while (__any_sync(0xffffffffu, ((w.x ^ tag2) | (w.y ^ tag2) | (w.z ^ tag2) | (w.w ^ tag2)) & 3u)) {
                    spun = true;
                    sp.tick(32);
                    w = ldx128(gate);
                }
            }
#pragma unroll
            for (int i = 0; i < NV; i++) v[i] = ldx128(src + i * DH);
#pragma unroll
            for (int i = 0; i < NV; i++)
                if (((v[i].x ^ tag2) | (v[i].y ^ tag2) | (v[i].z ^ tag2) | (v[i].w ^ tag2)) & 3u) pending |= 1u << i;
            waited = __any_sync(0xffffffffu, pending != 0);
            {
                while (__any_sync(0xffffffffu, pending != 0)) {
                    sp.tick(0);
#pragma unroll
                    for (int i = 0; i < NV; i++)
                        if (pending & (1u << i)) v[i] = ldx128(src + i * DH);
#pragma unroll
                    for (int i = 0; i < NV; i++)
                        if ((((v[i].x ^ tag2) | (v[i].y ^ tag2) | (v[i].z ^ tag2) | (v[i].w ^ tag2)) & 3u) == 0) pending &= ~(1u << i);
                }
            }
            waited |= spun;
            float s0 = 0.f, s1 = 0.f, s2 = 0.f, s3 = 0.f;
#pragma unroll
            for (int i = 0; i < NV; i++) {
                s0 += __uint_as_float(v[i].x & ~3u); s1 += __uint_as_float(v[i].y & ~3u);
                s2 += __uint_as_float(v[i].z & ~3u); s3 += __uint_as_float(v[i].w & ~3u);
            }
            const int st = rnd & 1;
            mbar_wait(bar_oempty + (pid * 2 + st) * 8, ((rnd >> 1) & 1) ^ 1);
            const uint32_t row = sb + P_O + (pid * 2 + st) * 256 + (16 * t + g) * 2;
            const uint32_t p01 = pack2(s0, s1), p23 = pack2(s2, s3);
            sts16(row, p01 & 0xFFFFu); sts16(row + 16, p01 >> 16);
            sts16(row + 128, p23 & 0xFFFFu); sts16(row + 144, p23 >> 16);
            __syncwarp();
            if (lane == 0) mbar_arrive(bar_ofull + (pid * 2 + st) * 8);
        }
    }
}

__global__ void __launch_bounds__(NTHREADS, 1) fused_decode_kernel(const __grid_constant__ Params P) {
    extern __shared__ __align__(1024) unsigned char smem[];
    const uint32_t sb = smem_u32(smem);
    const int tid = threadIdx.x, warp = tid >> 5, lane = tid & 31;
    const int cta = blockIdx.x;
    const bool is_special = cta < NSPEC;
    const int sc = cta - NSPEC;
    const uint32_t bar_full = sb + S_BAR, bar_aux = bar_full + NSLOT * 8, bar_empty = bar_aux + NSLOT * 8, bar_desc = bar_empty + NSLOT * 8;

    if (tid == 288) {
        TS(0);
        unsigned e = g_epoch[cta] + 1;
        g_epoch[cta] = e;
        sts32(sb + EPOCH_OFF, e);
    }
    if (is_special) {
        if (tid == 0) {
            for (int i = 0; i < NBUF; i++) mbar_init(sb + P_BAR + i * 8, 1);
            for (int i = 0; i < HG; i++) mbar_init(sb + P_BAR + (NBUF + i) * 8, 8);
            for (int i = 0; i < 2 * HG; i++) mbar_init(sb + P_BAR + (NBUF + HG + i) * 8, 1);
            for (int i = 0; i < 2 * HG; i++) mbar_init(sb + P_BAR + (NBUF + 3 * HG + i) * 8, 8);
            asm volatile("fence.mbarrier_init.release.cluster;" ::: "memory");
        }
        if (tid >= 32 && tid < 96) sts32(sb + P_ZERO + (tid - 32) * 4, 0u);
        __syncthreads();
        if (warp < 8) {
            special_cta(P, sb, lds32(sb + EPOCH_OFF), cta, tid);
        } else if (warp < 8 + HG) {
            special_poller(sb, lds32(sb + EPOCH_OFF), cta, warp - 8, lane);
        } else if (warp == 8 + HG && lane == 0) {
#pragma unroll 1
            for (int grp = 1; grp < NH / HG; grp++)
#pragma unroll 1
                for (int c = 0; c < HG; c++) {
                    mbar_wait(sb + P_BAR + (NBUF + c) * 8, (grp - 1) & 1);
                    chunk_tma(sb + P_RING + c * CH_BYTES, &P.tm_wo, (cta & 3) * 128, (grp * HG + c) * 128, sb + P_BAR + c * 8, true);
                }
        }
        return;
    }

    if (warp < 8) {
        const int g = lane >> 2, t = lane & 3;
        {
            const bool has_slice = sc < QH_STREAM * 8;
            uint4 xa, xb;
            if (has_slice) { xa = ldg128(P.x + warp * DM + lane * 8); xb = ldg128(P.x + warp * DM + 256 + lane * 8); }
            __syncthreads();
            if (has_slice) {
                const uint32_t epoch = lds32(sb + EPOCH_OFF);
                const uint32_t tag16 = epoch & 0xFFFFu;
                const uint32_t xn = sb + S_RED, rq = sb + S_RED + 8 * XN_PITCH;
                const uint32_t wst = sb + S_RING + (NSLOT - 1) * ITEM_BYTES;
                layernorm_row(xa, xb, xn + warp * XN_PITCH, lane);
                bar_sync256();
                uint32_t pph = 0;
#pragma unroll 1
                for (int slice = sc; slice < QH_STREAM * 8; slice += P.nstream, pph ^= 1) {
                    mbar_wait(sb + S_PBAR, pph);
                    float ca[4] = {0.f, 0.f, 0.f, 0.f};
#pragma unroll
                    for (int k2 = 0; k2 < 2; k2++) {
                        uint32_t b0, b1, b2, b3;
                        ldsm4(xn + (lane & 7) * XN_PITCH + (warp * 64 + k2 * 32 + (lane >> 3) * 8) * 2, b0, b1, b2, b3);
#pragma unroll
                        for (int k1 = 0; k1 < 2; k1++) {
                            uint32_t a0, a1, a2, a3;
                            ldsm4t(wst + (warp * 64 + k2 * 32 + k1 * 16 + (lane & 7) + ((lane >> 4) & 1) * 8) * 32 + ((lane >> 3) & 1) * 16, a0, a1, a2, a3);
                            mma16816(ca, a0, a1, a2, a3, k1 ? b2 : b0, k1 ? b3 : b1);
                        }
                    }
                    const uint32_t rb = rq + (warp * 8 * 20 + 2 * t * 20 + g) * 4;
                    sts32(rb, __float_as_uint(ca[0])); sts32(rb + 20 * 4, __float_as_uint(ca[1]));
                    sts32(rb + 32, __float_as_uint(ca[2])); sts32(rb + 20 * 4 + 32, __float_as_uint(ca[3]));
                    bar_sync256();
                    if (tid < 128) {
                        const int b = tid >> 4, col = tid & 15;
                        float s = 0.f;
#pragma unroll
                        for (int w = 0; w < 8; w++) s += __uint_as_float(lds32(rq + (w * 8 * 20 + b * 20 + col) * 4));
                        stx32(g_q + (b * NH + (slice >> 3)) * DH + (slice & 7) * 16 + col, (__float_as_uint(bf16r(s)) & 0xFFFF0000u) | tag16);
                    }
                    bar_sync256();
                    if (tid == 0 && slice + P.nstream < QH_STREAM * 8) {
                        mbar_expect_tx(sb + S_PBAR, 16384);
                        tma_2d(wst, &P.tm_wqs, (slice + P.nstream) * 16, 0, sb + S_PBAR, policy_evict_normal());
                        tma_2d(wst + 8192, &P.tm_wqs, (slice + P.nstream) * 16, 256, sb + S_PBAR, policy_evict_normal());
                    }
                }
            }
            __syncwarp();
            if (lane == 0) mbar_arrive(sb + S_PBAR + 8);
        }
        if (tid == 0) TS(1);
        uint32_t koff[4];
#pragma unroll
        for (int jj = 0; jj < 4; jj++) koff[jj] = (4 * (jj ^ (g & 1)) + t) * 16;
        const uint32_t krow = (warp * 16 + g) * 256;
        const int mj = lane >> 3, mr = lane & 7;
        const uint32_t vrow = (warp * 16 + 4 * (mr >> 1) + (mr & 1) + 2 * (mj >> 1)) * 256 + (mj & 1) * 128;
        uint32_t vmask[8];
#pragma unroll
        for (int i = 0; i < 8; i++) vmask[i] = (g == ((2 * t) ^ i) ? 0x0000FFFFu : 0u) | (g == ((2 * t + 1) ^ i) ? 0xFFFF0000u : 0u);
        const float scale = 0.08838834764831845f;

        int s = 0;
        uint32_t ph = 0;
        float o0[4] = {0.f, 0.f, 0.f, 0.f}, o1[4] = {0.f, 0.f, 0.f, 0.f};
#pragma unroll 1
        while (true) {
            mbar_wait(bar_full + s * 8, ph);
            const uint32_t desc = lds32(sb + S_DESC + s * 4);
            if (desc == STOPD) break;
            const uint32_t tile = sb + S_RING + s * ITEM_BYTES;
            const uint32_t qp = sb + S_QP + s * 256;
            const uint32_t red = sb + S_RED + s * 4096;
            mbar_wait(bar_aux + s * 8, ph);
            if (!(desc >> 31)) {
                float c0[4] = {0.f, 0.f, 0.f, 0.f}, c1[4] = {0.f, 0.f, 0.f, 0.f};
#pragma unroll
                for (int jj = 0; jj < 4; jj++) {
                    uint4 qf = lds128(qp + koff[jj]);
                    uint4 r = lds128(tile + krow + koff[jj]);
                    uint4 q8 = lds128(tile + krow + 2048 + koff[jj]);
                    mma16816(c0, r.x, q8.x, r.y, q8.y, qf.x, qf.y);
                    mma16816(c1, r.z, q8.z, r.w, q8.w, qf.z, qf.w);
                }
                float lo = (g & 1) ? c0[1] + c1[1] : c0[0] + c1[0];
                float hi = (g & 1) ? c0[3] + c1[3] : c0[2] + c1[2];
                float val = (t & 1) ? hi : lo;
                val = bf16r(bf16r(val) * scale);
                if (t < 2) sts32(red + (warp * 16 + g + 8 * t) * 4, __float_as_uint(val));
            } else {
                uint2 pp = lds64(qp + (warp * 16 + 4 * t) * 2);
#pragma unroll
                for (int i = 0; i < 8; i++) {
                    uint32_t a0, a1, a2, a3;
                    ldsm4t(tile + vrow + ((mr ^ i) << 4), a0, a1, a2, a3);
                    mma16816((i & 1) ? o1 : o0, a0, a1, a2, a3, pp.x & vmask[i], pp.y & vmask[i]);
                }
                if (desc & 1u) {
                    sts128(red + warp * 512 + lane * 16, __float_as_uint(o0[0] + o1[0]), __float_as_uint(o0[1] + o1[1]),
                           __float_as_uint(o0[2] + o1[2]), __float_as_uint(o0[3] + o1[3]));
#pragma unroll
                    for (int e = 0; e < 4; e++) { o0[e] = 0.f; o1[e] = 0.f; }
                }
            }
            __syncwarp();
            if (lane == 0) mbar_arrive(bar_empty + s * 8);
            if (++s == NSLOT) { s = 0; ph ^= 1; }
        }
        if (tid == 0) TS(3);
    } else if (warp == 8) {
        if (lane == 0) {
#pragma unroll 1
            for (int s = 0; s < NSLOT; s++) {
                mbar_init(bar_full + s * 8, 1);
                mbar_init(bar_aux + s * 8, 1);
                mbar_init(bar_empty + s * 8, 8);
                mbar_init(bar_desc + s * 8, 1);
            }
            mbar_init(sb + S_PBAR, 1);
            mbar_init(sb + S_PBAR + 8, 8);
            asm volatile("fence.mbarrier_init.release.cluster;" ::: "memory");
            if (sc < QH_STREAM * 8) {
                const uint32_t wst = sb + S_RING + (NSLOT - 1) * ITEM_BYTES;
                mbar_expect_tx(sb + S_PBAR, 16384);
                tma_2d(wst, &P.tm_wqs, sc * 16, 0, sb + S_PBAR, policy_evict_normal());
                tma_2d(wst + 8192, &P.tm_wqs, sc * 16, 256, sb + S_PBAR, policy_evict_normal());
            }
        }
        uint64_t pol = 0;
        uint32_t nxt0 = 0;
        if (lane == 0) {
            pol = policy_evict_first();
            const uint32_t d0 = decode_super(sc);
            const __nv_bfloat16* src = P.k + ((size_t)((d0 >> 8) & 0xFFu) * SK + (d0 & 0xFFu) * ITEM_KEYS) * DH;
#pragma unroll
            for (int hf = 0; hf < 2; hf++) {
                sts32(sb + S_DESC + hf * 4, d0 + hf);
                mbar_expect_tx(bar_full + hf * 8, ITEM_BYTES);
                bulk_load(sb + S_RING + hf * ITEM_BYTES, src + hf * (ITEM_KEYS * DH), ITEM_BYTES, bar_full + hf * 8, pol);
                mbar_arrive(bar_desc + hf * 8);
            }
            nxt0 = atomicAdd(&g_ticket, 1u);
        }
        __syncthreads();
        if (lane == 0) {
            const uint32_t epoch = lds32(sb + EPOCH_OFF);
            const uint32_t base = (epoch - 1) * (uint32_t)TOTAL_SUPER - (uint32_t)P.nstream;
            int cur = (int)(nxt0 - base);
            int s = 2 % NSLOT, sw = 0, it = 2;
            uint32_t ph = (NSLOT == 2) ? 0 : 1, phw = 0;
#pragma unroll 1
            while (cur < TOTAL_SUPER) {
                const uint32_t d0 = decode_super(cur);
                const __nv_bfloat16* src = ((d0 >> 31) ? P.v : P.k) + ((size_t)((d0 >> 8) & 0xFFu) * SK + (d0 & 0xFFu) * ITEM_KEYS) * DH;
                uint32_t nxt = 0;
#pragma unroll
                for (int hf = 0; hf < 2; hf++) {
                    if (it == NSLOT - 1) mbar_wait(sb + S_PBAR + 8, 0);
                    mbar_wait(bar_empty + s * 8, ph);
                    if (it >= WINF && cur < TOTAL_SUPER - TAIL_FREE * P.nstream) {
                        mbar_wait(bar_full + sw * 8, phw);
                        if (++sw == NSLOT) { sw = 0; phw ^= 1; }
                    }
                    sts32(sb + S_DESC + s * 4, d0 + hf);
                    mbar_expect_tx(bar_full + s * 8, ITEM_BYTES);
                    bulk_load(sb + S_RING + s * ITEM_BYTES, src + hf * (ITEM_KEYS * DH), ITEM_BYTES, bar_full + s * 8, pol);
                    mbar_arrive(bar_desc + s * 8);
                    if (hf == CFG_TICKET_HF) nxt = atomicAdd(&g_ticket, 1u);
                    if (++s == NSLOT) { s = 0; ph ^= 1; }
                    it++;
                }
                cur = (int)(nxt - base);
            }
#pragma unroll 1
            for (int k = 0; k < NSLOT; k++) {
                mbar_wait(bar_empty + s * 8, ph);
                sts32(sb + S_DESC + s * 4, STOPD);
                mbar_arrive(bar_desc + s * 8);
                if (k == 0) mbar_arrive(bar_full + s * 8);
                if (++s == NSLOT) { s = 0; ph ^= 1; }
            }
        }
    } else {
        __syncthreads();
        const int s = warp - 9;
        const uint32_t epoch = lds32(sb + EPOCH_OFF);
        const uint32_t tag16 = epoch & 0xFFFFu, tag2 = epoch & 3u;
        const uint32_t qp = sb + S_QP + s * 256;
        const uint32_t red = sb + S_RED + s * 4096;
        uint32_t ph = 0;
#pragma unroll 1
        while (true) {
            mbar_wait(bar_desc + s * 8, ph);
            const uint32_t desc = lds32(sb + S_DESC + s * 4);
            if (desc == STOPD) break;
            const int is_v = desc >> 31, mp = (desc >> 8) & 0xFF, ch = desc & 0xFF;
            if (!is_v) {
                const uint32_t* src = g_q + mp * DH + lane * 4;
                uint4 w = ldx128(src);
                Spin sp;
                while (__any_sync(0xffffffffu, ((w.x & 0xFFFFu) != tag16) | ((w.y & 0xFFFFu) != tag16) | ((w.z & 0xFFFFu) != tag16) | ((w.w & 0xFFFFu) != tag16))) {
                    sp.tick(100);
                    w = ldx128(src);
                }
                sts64(qp + lane * 8, (w.x >> 16) | (w.y & 0xFFFF0000u), (w.z >> 16) | (w.w & 0xFFFF0000u));
            } else {
                const uint32_t* src = g_sc + (size_t)mp * SK + ch * ITEM_KEYS + lane * 4;
                const unsigned long long* ssrc = g_st + mp * IPP + lane;
                uint4 w = ldx128(src);
                unsigned long long st = ldx64(ssrc);
                Spin sp;
                while (__any_sync(0xffffffffu, ((w.x & 0xFFFFu) != tag16) | ((w.y & 0xFFFFu) != tag16) | ((w.z & 0xFFFFu) != tag16) |
                                                   ((w.w & 0xFFFFu) != tag16) | (((uint32_t)(st >> 32) & 0xFFFFu) != tag16))) {
                    sp.tick(100);
                    w = ldx128(src);
                    st = ldx64(ssrc);
                }
                const float mi = bfhi((uint32_t)(st >> 32)), li = __uint_as_float((uint32_t)st);
                const float m = warp_max(mi);
                const float sum = warp_sum(li * expf(mi - m));
                const float p0 = expf(bfhi(w.x) - m) / sum, p1 = expf(bfhi(w.y) - m) / sum;
                const float p2 = expf(bfhi(w.z) - m) / sum, p3 = expf(bfhi(w.w) - m) / sum;
                sts64(qp + lane * 8, pack2(p0, p1), pack2(p2, p3));
            }
            __syncwarp();
            if (lane == 0) mbar_arrive(bar_aux + s * 8);
            mbar_wait(bar_empty + s * 8, ph);
            if (!is_v) {
                uint4 w = lds128(red + lane * 16);
                const float s0 = __uint_as_float(w.x), s1 = __uint_as_float(w.y), s2 = __uint_as_float(w.z), s3 = __uint_as_float(w.w);
                const float m = warp_max(fmaxf(fmaxf(s0, s1), fmaxf(s2, s3)));
                const float ms = (m == -INFINITY) ? 0.f : m;
                const float l = warp_sum((expf(s0 - ms) + expf(s1 - ms)) + (expf(s2 - ms) + expf(s3 - ms)));
                stx128(g_sc + (size_t)mp * SK + ch * ITEM_KEYS + lane * 4, w.x | tag16, w.y | tag16, w.z | tag16, w.w | tag16);
                if (lane == 0)
                    stx64(g_st + mp * IPP + ch, ((unsigned long long)((__float_as_uint(m) & 0xFFFF0000u) | tag16) << 32) | __float_as_uint(l));
            } else if (ch & 1) {
                float a0 = 0.f, a1 = 0.f, a2 = 0.f, a3 = 0.f;
#pragma unroll
                for (int w8 = 0; w8 < 8; w8++) {
                    uint4 w = lds128(red + w8 * 512 + lane * 16);
                    a0 += __uint_as_float(w.x); a1 += __uint_as_float(w.y); a2 += __uint_as_float(w.z); a3 += __uint_as_float(w.w);
                }
                stx128(g_op + ((size_t)mp * SPP + (ch >> 1)) * DH + lane * 4, (__float_as_uint(a0) & ~3u) | tag2, (__float_as_uint(a1) & ~3u) | tag2,
                       (__float_as_uint(a2) & ~3u) | tag2, (__float_as_uint(a3) & ~3u) | tag2);
            }
            ph ^= 1;
        }
    }
}

}

typedef CUresult (*EncodeTiledFn)(CUtensorMap*, CUtensorMapDataType, cuuint32_t, void*, const cuuint64_t*, const cuuint64_t*,
                                  const cuuint32_t*, const cuuint32_t*, CUtensorMapInterleave, CUtensorMapSwizzle,
                                  CUtensorMapL2promotion, CUtensorMapFloatOOBfill);

static void make_map(EncodeTiledFn enc, CUtensorMap* tm, const void* base, int rows, int cols, int box_cols, int box_rows, CUtensorMapSwizzle sw) {
    cuuint64_t dims[2] = {(cuuint64_t)cols, (cuuint64_t)rows};
    cuuint64_t strides[1] = {(cuuint64_t)cols * 2};
    cuuint32_t box[2] = {(cuuint32_t)box_cols, (cuuint32_t)box_rows};
    cuuint32_t estr[2] = {1, 1};
    enc(tm, CU_TENSOR_MAP_DATA_TYPE_BFLOAT16, 2, const_cast<void*>(base), dims, strides, box, estr, CU_TENSOR_MAP_INTERLEAVE_NONE, sw,
        CU_TENSOR_MAP_L2_PROMOTION_NONE, CU_TENSOR_MAP_FLOAT_OOB_FILL_NONE);
}

extern "C" void kernel_launch(void* const* d_in, const int* in_sizes, int n_in, void* d_out, int out_size) {
    (void)in_sizes; (void)n_in; (void)out_size;
    static int nsm = 0;
    static EncodeTiledFn enc = nullptr;
    if (nsm == 0) {
        int dev = 0;
        cudaGetDevice(&dev);
        cudaDeviceGetAttribute(&nsm, cudaDevAttrMultiProcessorCount, dev);
        cudaFuncSetAttribute(fused_decode_kernel, cudaFuncAttributeMaxDynamicSharedMemorySize, SMEM_BYTES);
        void* fn = nullptr;
        cudaDriverEntryPointQueryResult qr;
        cudaGetDriverEntryPoint("cuTensorMapEncodeTiled", &fn, cudaEnableDefault, &qr);
        enc = (EncodeTiledFn)fn;
    }
    Params P;
    make_map(enc, &P.tm_wqs, d_in[3], DM, NH * DH, 16, 256, CU_TENSOR_MAP_SWIZZLE_NONE);
    make_map(enc, &P.tm_wq, d_in[3], DM, NH * DH, 64, 128, CU_TENSOR_MAP_SWIZZLE_128B);
    make_map(enc, &P.tm_wo, d_in[4], NH * DH, DM, 64, 128, CU_TENSOR_MAP_SWIZZLE_128B);
    make_map(enc, &P.tm_w1, d_in[6], DM, FF, 64, 128, CU_TENSOR_MAP_SWIZZLE_128B);
    make_map(enc, &P.tm_w2, d_in[8], FF, DM, 64, 128, CU_TENSOR_MAP_SWIZZLE_128B);
    P.x = (const __nv_bfloat16*)d_in[0];
    P.k = (const __nv_bfloat16*)d_in[1];
    P.v = (const __nv_bfloat16*)d_in[2];
    P.b1 = (const __nv_bfloat16*)d_in[7];
    P.b2 = (const __nv_bfloat16*)d_in[9];
    P.out = (__nv_bfloat16*)d_out;
    int grid = nsm < MAX_CTAS ? nsm : MAX_CTAS;
    P.nstream = grid - NSPEC;
    fused_decode_kernel<<<grid, NTHREADS, SMEM_BYTES, cudaStreamPerThread>>>(P);
}
```

```cpp
#include <cuda_runtime.h>
#include <cuda.h>
#include <cuda_bf16.h>
#include <stdint.h>

namespace {

constexpr int NB = 8, NH = 32, SK = 4096, DH = 128, DM = 512, FF = 1792;
constexpr int NPAIR = NB * NH;

#define CFG_NSLOT 6
#define CFG_LAG 32
#define CFG_NU 4
#define CFG_W 2
#define CFG_TR 1
#define CFG_ALL_EF 0
#define CFG_SLEEP 1000
#define CFG_SLEEP_LAST 100
#define CFG_FINE 8
#define CFG_QH 8
constexpr int HG = 4;
constexpr int LAG = CFG_LAG;
constexpr int NSLOT = CFG_NSLOT;
constexpr int NU = CFG_NU;
constexpr int NSPEC = 4 * NU;
constexpr int ITEM_KEYS = 128;
constexpr int ITEM_BYTES = ITEM_KEYS * DH * 2;
constexpr int IPP = SK / ITEM_KEYS;
constexpr int SUP = 2;
constexpr int PPP = IPP / SUP;
constexpr int FINEP = CFG_FINE;
constexpr int TOTAL_TICKETS = NPAIR * PPP * 2 + FINEP * (IPP - PPP);
constexpr int NSTATIC = CFG_NSLOT / SUP;
constexpr int WINF = CFG_W;
constexpr int TR_GROUPS = CFG_TR;
constexpr int QH_STREAM = CFG_QH;
constexpr int NPOLL = 8;
constexpr int NWARPS = (9 + NSLOT > 8 + NPOLL) ? 9 + NSLOT : 8 + NPOLL;
constexpr int NTHREADS = NWARPS * 32;
constexpr int MAX_CTAS = 256;

constexpr int XN_PITCH = 1040;
constexpr int S_RING = 0;
constexpr int S_QP = S_RING + NSLOT * ITEM_BYTES;
constexpr int S_RED = S_QP + NSLOT * 256;
constexpr int PRO_BYTES = 8 * XN_PITCH + 8 * 8 * 20 * 4;
constexpr int RED_BYTES = (NSLOT * 4096 > PRO_BYTES) ? NSLOT * 4096 : PRO_BYTES;
constexpr int S_BAR = S_RED + RED_BYTES;
constexpr int S_PBAR = S_BAR + 4 * NSLOT * 8;
constexpr int S_DESC = S_PBAR + 16;
constexpr int S_EPOCH = S_DESC + NSLOT * 4;
constexpr int STREAM_SMEM = S_EPOCH + 16;

constexpr int CH_BYTES = 128 * 128 * 2;
constexpr int NBUF = 5;
constexpr int H_PITCH = FF * 2 + 16;
constexpr int P_RING = 0;
constexpr int P_XN = P_RING + NBUF * CH_BYTES;
constexpr int P_H = P_XN + 8 * XN_PITCH;
constexpr int P_O = P_H + 8 * H_PITCH;
constexpr int P_ZERO = P_O + 16 * 256;
constexpr int P_TMP = P_ZERO + 256;
constexpr int P_BAR = P_TMP + 4 * 512;
constexpr int P_GATE = P_BAR + (NBUF + HG + 36) * 8;
constexpr int P_END = P_GATE + 8;
constexpr int SMEM_BYTES = (((STREAM_SMEM > P_END + 16) ? STREAM_SMEM : P_END + 16) + 15) / 16 * 16;
constexpr int EPOCH_OFF = SMEM_BYTES - 16;
static_assert(SMEM_BYTES <= 232448, "smem");
static_assert(NSLOT % SUP == 0 && SMEM_BYTES % 16 == 0, "ring");
static_assert(NSLOT >= 4 && WINF >= 2 && WINF <= NSLOT, "ring");
static_assert(S_EPOCH <= EPOCH_OFF, "smem");

constexpr long long SPIN_LIMIT = 2000000000LL;

__device__ unsigned int g_epoch[MAX_CTAS];
__device__ unsigned int g_ticket;
__device__ __align__(128) uint32_t g_q[NPAIR * DH];
__device__ __align__(128) uint32_t g_sc[NPAIR * SK];
__device__ __align__(128) unsigned long long g_st[NPAIR * IPP];
__device__ __align__(128) uint32_t g_op[NPAIR * IPP * DH];
__device__ __align__(128) uint32_t g_h[NB * FF];

#define TS(i) do {} while (0)

__device__ __forceinline__ uint32_t smem_u32(const void* p) { return (uint32_t)__cvta_generic_to_shared(p); }
__device__ __forceinline__ float bf16r(float x) { return __bfloat162float(__float2bfloat16_rn(x)); }
__device__ __forceinline__ float bflo(uint32_t w) { return __uint_as_float(w << 16); }
__device__ __forceinline__ float bfhi(uint32_t w) { return __uint_as_float(w & 0xFFFF0000u); }
__device__ __forceinline__ uint32_t pack2(float lo, float hi) {
    uint32_t r;
    asm("cvt.rn.bf16x2.f32 %0, %1, %2;" : "=r"(r) : "f"(hi), "f"(lo));
    return r;
}
__device__ __forceinline__ void mbar_init(uint32_t bar, int cnt) {
    asm volatile("mbarrier.init.shared::cta.b64 [%0], %1;" ::"r"(bar), "r"(cnt) : "memory");
}
__device__ __forceinline__ void mbar_expect_tx(uint32_t bar, uint32_t bytes) {
    asm volatile("mbarrier.arrive.expect_tx.shared::cta.b64 _, [%0], %1;" ::"r"(bar), "r"(bytes) : "memory");
}
__device__ __forceinline__ void mbar_arrive(uint32_t bar) {
    asm volatile("mbarrier.arrive.shared::cta.b64 _, [%0];" ::"r"(bar) : "memory");
}
__device__ __forceinline__ bool mbar_try(uint32_t bar, uint32_t parity) {
    uint32_t ok;
    asm volatile(
        "{\n.reg .pred p;\nmbarrier.try_wait.parity.shared::cta.b64 p, [%1], %2;\nselp.u32 %0, 1, 0, p;\n}"
        : "=r"(ok) : "r"(bar), "r"(parity) : "memory");
    return ok != 0;
}
__device__ __forceinline__ void mbar_wait(uint32_t bar, uint32_t parity) {
    if (mbar_try(bar, parity)) return;
    long long t0 = clock64();
    while (!mbar_try(bar, parity)) {
        if (clock64() - t0 > SPIN_LIMIT) __trap();
    }
}
__device__ __forceinline__ void bulk_load(uint32_t dst, const void* src, uint32_t bytes, uint32_t bar, uint64_t pol) {
    asm volatile(
        "cp.async.bulk.shared::cluster.global.mbarrier::complete_tx::bytes.L2::cache_hint [%0], [%1], %2, [%3], %4;"
        ::"r"(dst), "l"(src), "r"(bytes), "r"(bar), "l"(pol) : "memory");
}
__device__ __forceinline__ void bar_sync256() { asm volatile("bar.sync 1, 256;" ::: "memory"); }

__device__ __forceinline__ uint4 lds128(uint32_t a) {
    uint4 v;
    asm volatile("ld.shared.v4.u32 {%0,%1,%2,%3}, [%4];" : "=r"(v.x), "=r"(v.y), "=r"(v.z), "=r"(v.w) : "r"(a));
    return v;
}
__device__ __forceinline__ uint2 lds64(uint32_t a) {
    uint2 v;
    asm volatile("ld.shared.v2.u32 {%0,%1}, [%2];" : "=r"(v.x), "=r"(v.y) : "r"(a));
    return v;
}
__device__ __forceinline__ uint32_t lds32(uint32_t a) {
    uint32_t v;
    asm volatile("ld.shared.u32 %0, [%1];" : "=r"(v) : "r"(a));
    return v;
}
__device__ __forceinline__ uint32_t lds32_volatile(uint32_t a) {
    uint32_t v;
    asm volatile("ld.volatile.shared.u32 %0, [%1];" : "=r"(v) : "r"(a) : "memory");
    return v;
}
__device__ __forceinline__ void sts128(uint32_t a, uint32_t x, uint32_t y, uint32_t z, uint32_t w) {
    asm volatile("st.shared.v4.u32 [%0], {%1,%2,%3,%4};" ::"r"(a), "r"(x), "r"(y), "r"(z), "r"(w) : "memory");
}
__device__ __forceinline__ void sts64(uint32_t a, uint32_t x, uint32_t y) {
    asm volatile("st.shared.v2.u32 [%0], {%1,%2};" ::"r"(a), "r"(x), "r"(y) : "memory");
}
__device__ __forceinline__ void sts32(uint32_t a, uint32_t x) {
    asm volatile("st.shared.u32 [%0], %1;" ::"r"(a), "r"(x) : "memory");
}
__device__ __forceinline__ void sts16(uint32_t a, uint32_t x) {
    asm volatile("st.shared.u16 [%0], %1;" ::"r"(a), "h"((unsigned short)x) : "memory");
}
__device__ __forceinline__ void ldsm4t(uint32_t a, uint32_t& r0, uint32_t& r1, uint32_t& r2, uint32_t& r3) {
    asm volatile("ldmatrix.sync.aligned.m8n8.x4.trans.shared.b16 {%0,%1,%2,%3}, [%4];"
                 : "=r"(r0), "=r"(r1), "=r"(r2), "=r"(r3) : "r"(a));
}
__device__ __forceinline__ void ldsm4(uint32_t a, uint32_t& r0, uint32_t& r1, uint32_t& r2, uint32_t& r3) {
    asm volatile("ldmatrix.sync.aligned.m8n8.x4.shared.b16 {%0,%1,%2,%3}, [%4];"
                 : "=r"(r0), "=r"(r1), "=r"(r2), "=r"(r3) : "r"(a));
}
__device__ __forceinline__ void mma16816(float* c, uint32_t a0, uint32_t a1, uint32_t a2, uint32_t a3, uint32_t b0, uint32_t b1) {
    asm volatile(
        "mma.sync.aligned.m16n8k16.row.col.f32.bf16.bf16.f32 {%0,%1,%2,%3}, {%4,%5,%6,%7}, {%8,%9}, {%0,%1,%2,%3};"
        : "+f"(c[0]), "+f"(c[1]), "+f"(c[2]), "+f"(c[3])
        : "r"(a0), "r"(a1), "r"(a2), "r"(a3), "r"(b0), "r"(b1));
}
__device__ __forceinline__ uint4 ldx128(const void* p) {
    uint4 v;
    asm volatile("ld.relaxed.gpu.global.v4.u32 {%0,%1,%2,%3}, [%4];" : "=r"(v.x), "=r"(v.y), "=r"(v.z), "=r"(v.w) : "l"(p) : "memory");
    return v;
}
__device__ __forceinline__ uint32_t ldx32(const void* p) {
    uint32_t v;
    asm volatile("ld.relaxed.gpu.global.u32 %0, [%1];" : "=r"(v) : "l"(p) : "memory");
    return v;
}
__device__ __forceinline__ unsigned ld_epoch(const unsigned* p) {
    unsigned v;
    asm volatile("ld.global.u32 %0, [%1];" : "=r"(v) : "l"(p));
    return v;
}
__device__ __forceinline__ unsigned long long ldx64(const void* p) {
    unsigned long long v;
    asm volatile("ld.relaxed.gpu.global.u64 %0, [%1];" : "=l"(v) : "l"(p) : "memory");
    return v;
}
__device__ __forceinline__ void stx128(void* p, uint32_t x, uint32_t y, uint32_t z, uint32_t w) {
    asm volatile("st.relaxed.gpu.global.v4.u32 [%0], {%1,%2,%3,%4};" ::"l"(p), "r"(x), "r"(y), "r"(z), "r"(w) : "memory");
}
__device__ __forceinline__ void stx64(void* p, unsigned long long v) {
    asm volatile("st.relaxed.gpu.global.u64 [%0], %1;" ::"l"(p), "l"(v) : "memory");
}
__device__ __forceinline__ void stx32(void* p, uint32_t v) {
    asm volatile("st.relaxed.gpu.global.u32 [%0], %1;" ::"l"(p), "r"(v) : "memory");
}
__device__ __forceinline__ uint4 ldg128(const void* p) {
    uint4 v;
    asm volatile("ld.global.nc.L1::no_allocate.v4.u32 {%0,%1,%2,%3}, [%4];" : "=r"(v.x), "=r"(v.y), "=r"(v.z), "=r"(v.w) : "l"(p));
    return v;
}
__device__ __forceinline__ float ldg_bf16(const __nv_bfloat16* p) { return __bfloat162float(__ldg(p)); }

__device__ __forceinline__ float warp_max(float v) {
#pragma unroll
    for (int o = 16; o > 0; o >>= 1) v = fmaxf(v, __shfl_xor_sync(0xffffffffu, v, o));
    return v;
}
__device__ __forceinline__ float warp_sum(float v) {
#pragma unroll
    for (int o = 16; o > 0; o >>= 1) v += __shfl_xor_sync(0xffffffffu, v, o);
    return v;
}
struct Spin {
    long long t0;
    __device__ __forceinline__ Spin() : t0(0) {}
    __device__ __forceinline__ void tick(unsigned ns) {
        if (t0 == 0) t0 = clock64();
        else if (clock64() - t0 > SPIN_LIMIT) __trap();
        if (ns) __nanosleep(ns);
    }
};

__device__ __forceinline__ uint32_t get_epoch(uint32_t sb) {
    mbar_wait(sb + EPOCH_OFF + 8, 0);
    return lds32(sb + EPOCH_OFF);
}
struct Params {
    CUtensorMap tm_wqs, tm_wq, tm_w1, tm_w2, tm_wo;
    const __nv_bfloat16 *x, *k, *v, *b1, *b2;
    __nv_bfloat16* out;
    int nstream;
};
__device__ __forceinline__ uint64_t policy_evict_first() {
    uint64_t pol;
    asm volatile("createpolicy.fractional.L2::evict_first.b64 %0, 1.0;" : "=l"(pol));
    return pol;
}
__device__ __forceinline__ uint64_t policy_evict_normal() {
    uint64_t pol;
    asm volatile("createpolicy.fractional.L2::evict_normal.b64 %0, 1.0;" : "=l"(pol));
    return pol;
}
__device__ __forceinline__ void tma_2d(uint32_t dst, const CUtensorMap* tm, int x, int y, uint32_t bar, uint64_t pol) {
    asm volatile("cp.async.bulk.tensor.2d.shared::cluster.global.tile.mbarrier::complete_tx::bytes.L2::cache_hint [%0], [%1, {%2, %3}], [%4], %5;"
                 ::"r"(dst), "l"(tm), "r"(x), "r"(y), "r"(bar), "l"(pol) : "memory");
}
__device__ __forceinline__ void chunk_tma(uint32_t dst, const CUtensorMap* tm, int col, int row, uint32_t bar, bool shared_by_many) {
    const uint64_t pol = (shared_by_many && !CFG_ALL_EF) ? policy_evict_normal() : policy_evict_first();
    mbar_expect_tx(bar, CH_BYTES);
    tma_2d(dst, tm, col, row, bar, pol);
    tma_2d(dst + CH_BYTES / 2, tm, col + 64, row, bar, pol);
}

constexpr uint32_t D_V = 1u << 31, D_FINE = 1u << 30;
__device__ __forceinline__ uint32_t decode_ticket(int idx) {
    constexpr int A = LAG * PPP;
    constexpr int MID = (NPAIR - LAG) * PPP * 2;
    constexpr int C = (LAG - FINEP) * PPP;
    int p, ch;
    uint32_t flags;
    if (idx < A) {
        flags = 0; p = idx / PPP; ch = (idx % PPP) * SUP;
    } else if (idx < A + MID) {
        int j = idx - A;
        flags = (j & 1) ? 0u : D_V;
        ch = ((j >> 1) % PPP) * SUP;
        p = j / (2 * PPP) + ((j & 1) ? LAG : 0);
    } else if (idx < A + MID + C) {
        int j = idx - A - MID;
        flags = D_V; p = NPAIR - LAG + j / PPP; ch = (j % PPP) * SUP;
    } else {
        int j = idx - A - MID - C;
        flags = D_V | D_FINE; p = NPAIR - FINEP + j / IPP; ch = j % IPP;
    }
    const int grp = p / (8 * HG), r = p % (8 * HG);
    const bool tr = grp >= NH / HG - TR_GROUPS;
    const int b = tr ? r % 8 : r / HG, h = grp * HG + (tr ? r / 8 : r % HG);
    return flags | ((uint32_t)(b * NH + h) << 8) | (uint32_t)ch;
}
constexpr uint32_t STOPD = 0x7FFFFFFFu;

__device__ __forceinline__ void layernorm_row(uint4 xa, uint4 xb, uint32_t dst_row, int lane) {
    float v[16];
    v[0] = bflo(xa.x); v[1] = bfhi(xa.x); v[2] = bflo(xa.y); v[3] = bfhi(xa.y);
    v[4] = bflo(xa.z); v[5] = bfhi(xa.z); v[6] = bflo(xa.w); v[7] = bfhi(xa.w);
    v[8] = bflo(xb.x); v[9] = bfhi(xb.x); v[10] = bflo(xb.y); v[11] = bfhi(xb.y);
    v[12] = bflo(xb.z); v[13] = bfhi(xb.z); v[14] = bflo(xb.w); v[15] = bfhi(xb.w);
    float s = 0.f;
#pragma unroll
    for (int i = 0; i < 16; i++) s += v[i];
    s = warp_sum(s);
    const float mean = s * (1.0f / DM);
    float q = 0.f;
#pragma unroll
    for (int i = 0; i < 16; i++) { float d = v[i] - mean; q += d * d; }
    q = warp_sum(q);
    const float m = bf16r(mean);
    const float var = bf16r(q * (1.0f / DM));
    const float den = bf16r(sqrtf(bf16r(var + 1e-5f)));
    uint32_t o[8];
#pragma unroll
    for (int i = 0; i < 8; i++) {
        float a = bf16r(v[2 * i] - m) / den;
        float b = bf16r(v[2 * i + 1] - m) / den;
        o[i] = pack2(a, b);
    }
    sts128(dst_row + lane * 16, o[0], o[1], o[2], o[3]);
    sts128(dst_row + 512 + lane * 16, o[4], o[5], o[6], o[7]);
}

__device__ __forceinline__ void chunk_load_a(uint32_t (&a)[8][4], uint32_t chunk, int warp, int lane) {
    const uint32_t a_addr = chunk + (warp >> 2) * (CH_BYTES / 2) + ((lane & 7) + ((lane >> 4) & 1) * 8) * 128 +
                            ((((warp & 3) * 2 + ((lane >> 3) & 1)) ^ (lane & 7)) << 4);
#pragma unroll
    for (int ks = 0; ks < 8; ks++) ldsm4t(a_addr + ks * 16 * 128, a[ks][0], a[ks][1], a[ks][2], a[ks][3]);
}
__device__ __forceinline__ void chunk_mma_b(float (&acc)[4][4], const uint32_t (&a)[8][4], uint32_t b_addr) {
    uint32_t bb[4][4];
#pragma unroll
    for (int q = 0; q < 4; q++) ldsm4(b_addr + q * 64, bb[q][0], bb[q][1], bb[q][2], bb[q][3]);
#pragma unroll
    for (int ks = 0; ks < 8; ks++)
        mma16816(acc[ks & 3], a[ks][0], a[ks][1], a[ks][2], a[ks][3], bb[ks >> 1][(ks & 1) * 2], bb[ks >> 1][(ks & 1) * 2 + 1]);
}
__device__ __forceinline__ void chunk_mma(float (&acc)[4][4], uint32_t chunk, uint32_t act, int act_pitch, int warp, int lane) {
    uint32_t a[8][4];
    chunk_load_a(a, chunk, warp, lane);
    chunk_mma_b(acc, a, act + (lane & 7) * act_pitch + (lane >> 3) * 16);
}
__device__ __forceinline__ float acc_sum(const float (&acc)[4][4], int e) { return (acc[0][e] + acc[1][e]) + (acc[2][e] + acc[3][e]); }
__device__ __forceinline__ void acc_zero(float (&acc)[4][4]) {
#pragma unroll
    for (int i = 0; i < 4; i++)
#pragma unroll
        for (int e = 0; e < 4; e++) acc[i][e] = 0.f;
}
__device__ __forceinline__ float gelu_tanh(float x) {
    const float kBeta = 0.7978845608028654f, kKappa = 0.044715f;
    float inner = kBeta * (x + kKappa * x * x * x);
    return 0.5f * x * (1.0f + tanhf(inner));
}

__device__ __forceinline__ void pair_seq(int n, int& grp, int& hl, int& bi) {
    constexpr int RPG = NB / NU;
    grp = n / (RPG * HG);
    const int q = n % (RPG * HG);
    const bool tr = grp >= NH / HG - TR_GROUPS;
    hl = tr ? q / RPG : q % HG;
    bi = tr ? q % RPG : q / HG;
}
constexpr int NSEQ = NPAIR / NU;
constexpr int NOB = NPOLL;
static_assert(TR_GROUPS == 1 && FINEP <= 8 * HG && FINEP <= LAG && PPP == 16, "pair order");
__device__ void special_cta(const Params& P, uint32_t sb, int sidx, int tid, uint4 xa, uint4 xb) {
    const int warp = tid >> 5, lane = tid & 31, g = lane >> 2, t = lane & 3;
    const int j = sidx & 3;
    const int u = sidx >> 2;

    const int nq = (NH - QH_STREAM - sidx + NSPEC - 1) / NSPEC;
    const int nslab = (FF / 128 - sidx + NSPEC - 1) / NSPEC;
    const int n0 = nq * 4, n1 = n0 + nslab * 4, ntot = n1 + FF / 128;
    const uint32_t pbar = sb + P_BAR;
    auto issue = [&](int i) {
        if (i < ntot) {
            const uint32_t dst = sb + P_RING + (i % NBUF) * CH_BYTES, bar = pbar + (i % NBUF) * 8;
            if (i < n0) chunk_tma(dst, &P.tm_wq, (QH_STREAM + sidx + (i >> 2) * NSPEC) * 128, (i & 3) * 128, bar, false);
            else if (i < n1) chunk_tma(dst, &P.tm_w1, (sidx + ((i - n0) >> 2) * NSPEC) * 128, (i & 3) * 128, bar, false);
            else chunk_tma(dst, &P.tm_w2, j * 128, (i - n1) * 128, bar, true);
        }
    };
    if (tid == 0) {
#pragma unroll 1
        for (int i = 0; i < NBUF - 1; i++) issue(i);
    }
    uint32_t par = 0;
    layernorm_row(xa, xb, sb + P_XN + warp * XN_PITCH, lane);
    const uint32_t tag16 = get_epoch(sb) & 0xFFFFu;
    float acc[4][4];
    acc_zero(acc);
#pragma unroll 1
    for (int i = 0; i < ntot; i++) {
        if (i == n1) {
            Spin sp;
#pragma unroll 1
            for (int c0 = tid; c0 < NB * FF / 4; c0 += 256 * 7) {
                uint4 w[7];
#pragma unroll
                for (int q = 0; q < 7; q++) w[q] = ldx128(g_h + (c0 + q * 256) * 4);
#pragma unroll
                for (int q = 0; q < 7; q++) {
                    const int c = c0 + q * 256;
                    while (((w[q].x & 0xFFFFu) != tag16) | ((w[q].y & 0xFFFFu) != tag16) | ((w[q].z & 0xFFFFu) != tag16) | ((w[q].w & 0xFFFFu) != tag16)) {
                        sp.tick(100);
                        w[q] = ldx128(g_h + c * 4);
                    }
                    int b = c / (FF / 4), col = (c % (FF / 4)) * 4;
                    sts64(sb + P_H + b * H_PITCH + col * 2, (w[q].x >> 16) | (w[q].y & 0xFFFF0000u), (w[q].z >> 16) | (w[q].w & 0xFFFF0000u));
                }
            }
        }
        bar_sync256();
        if (tid == 0) issue(i + NBUF - 1);
        const int sl = i % NBUF;
        mbar_wait(pbar + sl * 8, (par >> sl) & 1u);
        par ^= 1u << sl;
        uint32_t chunk = sb + P_RING + sl * CH_BYTES;
        if (i < n1) {
            chunk_mma(acc, chunk, sb + P_XN + (i & 3) * 256, XN_PITCH, warp, lane);
            if ((i & 3) == 3) {
                if (i < n0) {
                    const int h = QH_STREAM + sidx + (i >> 2) * NSPEC;
#pragma unroll
                    for (int e = 0; e < 4; e++) {
                        int c = warp * 16 + g + (e >> 1) * 8, b = 2 * t + (e & 1);
                        stx32(g_q + (b * NH + h) * DH + c, (__float_as_uint(bf16r(acc_sum(acc, e))) & 0xFFFF0000u) | tag16);
                    }
                } else {
                    const int col = (sidx + ((i - n0) >> 2) * NSPEC) * 128 + warp * 16 + g;
#pragma unroll
                    for (int e = 0; e < 4; e++) {
                        int c = col + (e >> 1) * 8, b = 2 * t + (e & 1);
                        float hp = bf16r(acc_sum(acc, e));
                        float hb = bf16r(hp + ldg_bf16(P.b1 + c));
                        float gl = bf16r(gelu_tanh(hb));
                        stx32(g_h + b * FF + c, (__float_as_uint(gl) & 0xFFFF0000u) | tag16);
                    }
                }
                acc_zero(acc);
            }
        } else {
            chunk_mma(acc, chunk, sb + P_H + (i - n1) * 256, H_PITCH, warp, lane);
        }
    }
    const int col0 = j * 128 + warp * 16 + g;
    float ffn[4], xin[4];
#pragma unroll
    for (int e = 0; e < 4; e++) {
        int c = col0 + (e >> 1) * 8, b = 2 * t + (e & 1);
        ffn[e] = bf16r(bf16r(acc_sum(acc, e)) + ldg_bf16(P.b2 + c));
        xin[e] = ldg_bf16(P.x + b * DM + c);
    }
    acc_zero(acc);
    __nv_bfloat16* outp = P.out + col0;
    asm volatile("" : "+l"(outp));
    if (tid == 0) TS(2);
    bar_sync256();
    if (tid == 0) {
#pragma unroll 1
        for (int c = 0; c < HG; c++) chunk_tma(sb + P_RING + c * CH_BYTES, &P.tm_wo, j * 128, c * 128, pbar + c * 8, true);
    }
    const uint32_t bar_cempty = pbar + NBUF * 8, bar_ofull = bar_cempty + HG * 8, bar_oempty = bar_ofull + 128;
    constexpr int RPG = NB / NU;
    uint32_t a[8][4];
    int a_head = -1;
#pragma unroll 1
    for (int n = 0; n < NPAIR / NU; n++) {
        int grp, hl, bi;
        pair_seq(n, grp, hl, bi);
        const int b = u + bi * NU;
        const int ob = (n % NOB) * 2 + ((n / NOB) & 1);
        if (grp * HG + hl != a_head) {
            if (bi == 0) mbar_wait(pbar + hl * 8, ((par >> hl) ^ grp) & 1u);
            chunk_load_a(a, sb + P_RING + hl * CH_BYTES, warp, lane);
            a_head = grp * HG + hl;
        }
        mbar_wait(bar_ofull + ob * 8, (n / (2 * NOB)) & 1);
        const uint32_t b_addr = ((lane & 7) == b ? sb + P_O + ob * 256 : sb + P_ZERO) + (lane >> 3) * 16;
        chunk_mma_b(acc, a, b_addr);
        __syncwarp();
        if (lane == 0) {
            mbar_arrive(bar_oempty + ob * 8);
            if (bi == RPG - 1 && grp + 1 < NH / HG) {
                mbar_arrive(bar_cempty + hl * 8);
                if (warp == hl) {
                    mbar_wait(bar_cempty + hl * 8, grp & 1);
                    chunk_tma(sb + P_RING + hl * CH_BYTES, &P.tm_wo, j * 128, ((grp + 1) * HG + hl) * 128, pbar + hl * 8, true);
                }
            }
        }
        __syncwarp();
    }
    if (tid == 0) TS(3);
#pragma unroll
    for (int e = 0; e < 4; e++) {
        const int b = 2 * t + (e & 1);
        if (b % NU == u) {
            float a = bf16r(acc_sum(acc, e));
            float r = bf16r(bf16r(xin[e] + a) + ffn[e]);
            outp[b * DM + (e >> 1) * 8] = __float2bfloat16_rn(r);
        }
    }
    if (tid == 0) TS(4);
}

__device__ __forceinline__ void fold16(const uint32_t* src, uint32_t tag2, unsigned sleep_ns, Spin& sp, float (&s)[4]) {
    constexpr int NV = 16;
    uint4 v[NV];
    uint32_t pending = 0;
#pragma unroll
    for (int i = 0; i < NV; i++) v[i] = ldx128(src + i * DH);
#pragma unroll
    for (int i = 0; i < NV; i++)
        if (((v[i].x ^ tag2) | (v[i].y ^ tag2) | (v[i].z ^ tag2) | (v[i].w ^ tag2)) & 3u) pending |= 1u << i;
    while (__any_sync(0xffffffffu, pending != 0)) {
        sp.tick(sleep_ns);
#pragma unroll
        for (int i = 0; i < NV; i++)
            if (pending & (1u << i)) v[i] = ldx128(src + i * DH);
#pragma unroll
        for (int i = 0; i < NV; i++)
            if ((((v[i].x ^ tag2) | (v[i].y ^ tag2) | (v[i].z ^ tag2) | (v[i].w ^ tag2)) & 3u) == 0) pending &= ~(1u << i);
    }
    s[0] = s[1] = s[2] = s[3] = 0.f;
#pragma unroll
    for (int i = 0; i < NV; i++) {
        s[0] += __uint_as_float(v[i].x & ~3u); s[1] += __uint_as_float(v[i].y & ~3u);
        s[2] += __uint_as_float(v[i].z & ~3u); s[3] += __uint_as_float(v[i].w & ~3u);
    }
}
__device__ __forceinline__ void wait_word(const uint32_t* p, uint32_t tag2, unsigned sleep_ns, Spin& sp) {
    uint32_t w = ldx32(p);
    while ((w ^ tag2) & 3u) {
        sp.tick(sleep_ns);
        w = ldx32(p);
    }
}
constexpr int NFINE = FINEP / NU;
static_assert(NFINE <= NPOLL / 2 && FINEP % 8 == 0, "fine pairs");

__device__ void special_poller(uint32_t sb, uint32_t epoch, int sidx, int pid, int lane) {
    const int u = sidx >> 2, g = lane >> 2, t = lane & 3;
    const uint32_t tag2 = epoch & 3u;
    const uint32_t pbar = sb + P_BAR;
    const uint32_t bar_ofull = pbar + (NBUF + HG) * 8, bar_oempty = bar_ofull + 128, bar_hfull = bar_oempty + 128;
#pragma unroll 1
    for (int n = pid; n < NSEQ + NOB; n += NOB) {
        const bool helper = n >= NSEQ;
        if (helper) {
            if (pid >= NFINE) break;
            n = NSEQ - NFINE + pid;
        }
        int grp, hl, bi;
        pair_seq(n, grp, hl, bi);
        const int b = u + bi * NU;
        const int ob = (n % NOB) * 2 + ((n / NOB) & 1);
        const uint32_t oph = (n / (2 * NOB)) & 1;
        const bool last = grp == NH / HG - 1;
        const uint32_t* src = g_op + ((size_t)(b * NH + grp * HG + hl) * IPP + (helper ? 16 : 0)) * DH + lane * 4;
        Spin sp;
        if (last) {
            while ((int)lds32_volatile(sb + P_GATE) < NSEQ - (NB / NU) * HG) sp.tick(64);
            wait_word(src - lane * 4, tag2, CFG_SLEEP_LAST, sp);
        } else {
            while ((int)lds32_volatile(sb + P_GATE) < n) sp.tick(64);
            wait_word(src - lane * 4 + (PPP - 1) * DH, tag2, CFG_SLEEP, sp);
            if (lane == 0) sts32(sb + P_GATE, (uint32_t)(n + 1));
        }
        float s[4];
        fold16(src, tag2, last ? 0 : CFG_SLEEP, sp, s);
        if (helper) {
            sts128(sb + P_TMP + pid * 512 + lane * 16, __float_as_uint(s[0]), __float_as_uint(s[1]), __float_as_uint(s[2]), __float_as_uint(s[3]));
            __syncwarp();
            if (lane == 0) mbar_arrive(bar_hfull + pid * 8);
            break;
        }
        if (n >= NSEQ - NFINE) {
            const int hp = n - (NSEQ - NFINE);
            mbar_wait(bar_hfull + hp * 8, 0);
            const uint4 o = lds128(sb + P_TMP + hp * 512 + lane * 16);
            s[0] += __uint_as_float(o.x); s[1] += __uint_as_float(o.y); s[2] += __uint_as_float(o.z); s[3] += __uint_as_float(o.w);
        }
        mbar_wait(bar_oempty + ob * 8, oph ^ 1);
        const uint32_t row = sb + P_O + ob * 256 + (16 * t + g) * 2;
        const uint32_t p01 = pack2(s[0], s[1]), p23 = pack2(s[2], s[3]);
        sts16(row, p01 & 0xFFFFu); sts16(row + 16, p01 >> 16);
        sts16(row + 128, p23 & 0xFFFFu); sts16(row + 144, p23 >> 16);
        __syncwarp();
        if (lane == 0) mbar_arrive(bar_ofull + ob * 8);
    }
}

__global__ void __launch_bounds__(NTHREADS, 1) fused_decode_kernel(const __grid_constant__ Params P) {
    extern __shared__ __align__(1024) unsigned char smem[];
    const uint32_t sb = smem_u32(smem);
    const int tid = threadIdx.x, warp = tid >> 5, lane = tid & 31;
    const int cta = blockIdx.x;
    const bool is_special = cta < NSPEC;
    const int sc = cta - NSPEC;
    const uint32_t bar_full = sb + S_BAR, bar_aux = bar_full + NSLOT * 8, bar_empty = bar_aux + NSLOT * 8, bar_desc = bar_empty + NSLOT * 8;

    if (tid == 256 && !is_special) {
        TS(0);
        mbar_init(bar_full, 1);
        mbar_init(bar_full + 8, 1);
        mbar_init(sb + S_PBAR, 1);
        asm volatile("fence.mbarrier_init.release.cluster;" ::: "memory");
        if (sc < QH_STREAM * 8) {
            const uint32_t wst = sb + S_RING + (NSLOT - 1) * ITEM_BYTES;
            mbar_expect_tx(sb + S_PBAR, 16384);
            tma_2d(wst, &P.tm_wqs, sc * 16, 0, sb + S_PBAR, policy_evict_normal());
            tma_2d(wst + 8192, &P.tm_wqs, sc * 16, 256, sb + S_PBAR, policy_evict_normal());
        }
        static_assert(HG == 4 && PPP == 16 && SUP == 2 && LAG * PPP >= MAX_CTAS, "static first ticket");
        const uint64_t pol = policy_evict_first();
        const uint32_t d0 = (uint32_t)((((sc >> 6) * NH + ((sc >> 4) & 3)) << 8) | ((sc & 15) * 2));
        const __nv_bfloat16* src = P.k + ((size_t)(d0 >> 8) * SK + (d0 & 0xFFu) * ITEM_KEYS) * DH;
#pragma unroll
        for (int i = 0; i < 2; i++) {
            mbar_expect_tx(bar_full + i * 8, ITEM_BYTES);
            bulk_load(sb + S_RING + i * ITEM_BYTES, src + i * (ITEM_KEYS * DH), ITEM_BYTES, bar_full + i * 8, pol);
        }
        sts32(sb + S_DESC, d0);
        sts32(sb + S_DESC + 4, d0 + 1);
        TS(5);
    }
    uint4 xa = make_uint4(0, 0, 0, 0), xb = xa;
    if (warp < 8 && (is_special || sc < QH_STREAM * 8)) {
        xa = ldg128(P.x + warp * DM + lane * 8);
        xb = ldg128(P.x + warp * DM + 256 + lane * 8);
    }
    unsigned e_prev = 0;
    if (tid == 288) {
        if (is_special) TS(0);
        e_prev = ld_epoch(&g_epoch[cta]);
        mbar_init(sb + EPOCH_OFF + 8, 1);
        asm volatile("fence.mbarrier_init.release.cluster;" ::: "memory");
    }
    auto publish_epoch = [&]() {
        if (tid == 288) {
            g_epoch[cta] = e_prev + 1;
            sts32(sb + EPOCH_OFF, e_prev + 1);
            mbar_arrive(sb + EPOCH_OFF + 8);
        }
    };
    if (is_special) {
        if (tid == 0) {
            for (int i = 0; i < NBUF; i++) mbar_init(sb + P_BAR + i * 8, 1);
            for (int i = 0; i < HG; i++) mbar_init(sb + P_BAR + (NBUF + i) * 8, 8);
            for (int i = 0; i < 16; i++) mbar_init(sb + P_BAR + (NBUF + HG + i) * 8, 1);
            for (int i = 0; i < 16; i++) mbar_init(sb + P_BAR + (NBUF + HG + 16 + i) * 8, 8);
            for (int i = 0; i < 4; i++) mbar_init(sb + P_BAR + (NBUF + HG + 32 + i) * 8, 1);
            asm volatile("fence.mbarrier_init.release.cluster;" ::: "memory");
        }
        if (tid >= 32 && tid < 96) sts32(sb + P_ZERO + (tid - 32) * 4, 0u);
        if (tid == 96) sts32(sb + P_GATE, 0u);
        __syncthreads();
        publish_epoch();
        if (warp < 8) {
            special_cta(P, sb, cta, tid, xa, xb);
        } else if (warp < 8 + NPOLL) {
            special_poller(sb, get_epoch(sb), cta, warp - 8, lane);
        }
        return;
    }

    if (warp < 8) {
        const int g = lane >> 2, t = lane & 3;
        {
            const bool has_slice = sc < QH_STREAM * 8;
            __syncthreads();
            if (has_slice) {
                const uint32_t xn = sb + S_RED, rq = sb + S_RED + 8 * XN_PITCH;
                const uint32_t wst = sb + S_RING + (NSLOT - 1) * ITEM_BYTES;
                layernorm_row(xa, xb, xn + warp * XN_PITCH, lane);
                bar_sync256();
                uint32_t pph = 0;
#pragma unroll 1
                for (int slice = sc; slice < QH_STREAM * 8; slice += P.nstream, pph ^= 1) {
                    mbar_wait(sb + S_PBAR, pph);
                    float ca[4] = {0.f, 0.f, 0.f, 0.f};
#pragma unroll
                    for (int k2 = 0; k2 < 2; k2++) {
                        uint32_t b0, b1, b2, b3;
                        ldsm4(xn + (lane & 7) * XN_PITCH + (warp * 64 + k2 * 32 + (lane >> 3) * 8) * 2, b0, b1, b2, b3);
#pragma unroll
                        for (int k1 = 0; k1 < 2; k1++) {
                            uint32_t a0, a1, a2, a3;
                            ldsm4t(wst + (warp * 64 + k2 * 32 + k1 * 16 + (lane & 7) + ((lane >> 4) & 1) * 8) * 32 + ((lane >> 3) & 1) * 16, a0, a1, a2, a3);
                            mma16816(ca, a0, a1, a2, a3, k1 ? b2 : b0, k1 ? b3 : b1);
                        }
                    }
                    const uint32_t rb = rq + (warp * 8 * 20 + 2 * t * 20 + g) * 4;
                    sts32(rb, __float_as_uint(ca[0])); sts32(rb + 20 * 4, __float_as_uint(ca[1]));
                    sts32(rb + 32, __float_as_uint(ca[2])); sts32(rb + 20 * 4 + 32, __float_as_uint(ca[3]));
                    bar_sync256();
                    if (tid < 128) {
                        const int b = tid >> 4, col = tid & 15;
                        float s = 0.f;
#pragma unroll
                        for (int w = 0; w < 8; w++) s += __uint_as_float(lds32(rq + (w * 8 * 20 + b * 20 + col) * 4));
                        stx32(g_q + (b * NH + (slice >> 3)) * DH + (slice & 7) * 16 + col,
                              (__float_as_uint(bf16r(s)) & 0xFFFF0000u) | (get_epoch(sb) & 0xFFFFu));
                    }
                    bar_sync256();
                    if (tid == 0 && slice + P.nstream < QH_STREAM * 8) {
                        mbar_expect_tx(sb + S_PBAR, 16384);
                        tma_2d(wst, &P.tm_wqs, (slice + P.nstream) * 16, 0, sb + S_PBAR, policy_evict_normal());
                        tma_2d(wst + 8192, &P.tm_wqs, (slice + P.nstream) * 16, 256, sb + S_PBAR, policy_evict_normal());
                    }
                }
            }
            __syncwarp();
            if (lane == 0) mbar_arrive(sb + S_PBAR + 8);
        }
        if (tid == 0) TS(1);
        uint32_t koff[4];
#pragma unroll
        for (int jj = 0; jj < 4; jj++) koff[jj] = (4 * (jj ^ (g & 1)) + t) * 16;
        const uint32_t krow = (warp * 16 + g) * 256;
        const int mj = lane >> 3, mr = lane & 7;
        const uint32_t vrow = (warp * 16 + 4 * (mr >> 1) + (mr & 1) + 2 * (mj >> 1)) * 256 + (mj & 1) * 128;
        uint32_t vmask[8];
#pragma unroll
        for (int i = 0; i < 8; i++) vmask[i] = (g == ((2 * t) ^ i) ? 0x0000FFFFu : 0u) | (g == ((2 * t + 1) ^ i) ? 0xFFFF0000u : 0u);
        const float scale = 0.08838834764831845f;

        int s = 0;
        uint32_t ph = 0;
        float o0[4] = {0.f, 0.f, 0.f, 0.f}, o1[4] = {0.f, 0.f, 0.f, 0.f};
#pragma unroll 1
        while (true) {
            mbar_wait(bar_full + s * 8, ph);
            const uint32_t desc = lds32(sb + S_DESC + s * 4);
            if (desc == STOPD) break;
            const uint32_t tile = sb + S_RING + s * ITEM_BYTES;
            const uint32_t qp = sb + S_QP + s * 256;
            const uint32_t red = sb + S_RED + s * 4096;
            mbar_wait(bar_aux + s * 8, ph);
            if (!(desc >> 31)) {
                float c0[4] = {0.f, 0.f, 0.f, 0.f}, c1[4] = {0.f, 0.f, 0.f, 0.f};
#pragma unroll
                for (int jj = 0; jj < 4; jj++) {
                    uint4 qf = lds128(qp + koff[jj]);
                    uint4 r = lds128(tile + krow + koff[jj]);
                    uint4 q8 = lds128(tile + krow + 2048 + koff[jj]);
                    mma16816(c0, r.x, q8.x, r.y, q8.y, qf.x, qf.y);
                    mma16816(c1, r.z, q8.z, r.w, q8.w, qf.z, qf.w);
                }
                float lo = (g & 1) ? c0[1] + c1[1] : c0[0] + c1[0];
                float hi = (g & 1) ? c0[3] + c1[3] : c0[2] + c1[2];
                float val = (t & 1) ? hi : lo;
                val = bf16r(bf16r(val) * scale);
                if (t < 2) sts32(red + (warp * 16 + g + 8 * t) * 4, __float_as_uint(val));
            } else {
                uint2 pp = lds64(qp + (warp * 16 + 4 * t) * 2);
#pragma unroll
                for (int i = 0; i < 8; i++) {
                    uint32_t a0, a1, a2, a3;
                    ldsm4t(tile + vrow + ((mr ^ i) << 4), a0, a1, a2, a3);
                    mma16816((i & 1) ? o1 : o0, a0, a1, a2, a3, pp.x & vmask[i], pp.y & vmask[i]);
                }
                if (desc & (D_FINE | 1u)) {
                    sts128(red + warp * 512 + lane * 16, __float_as_uint(o0[0] + o1[0]), __float_as_uint(o0[1] + o1[1]),
                           __float_as_uint(o0[2] + o1[2]), __float_as_uint(o0[3] + o1[3]));
#pragma unroll
                    for (int e = 0; e < 4; e++) { o0[e] = 0.f; o1[e] = 0.f; }
                }
            }
            __syncwarp();
            if (lane == 0) mbar_arrive(bar_empty + s * 8);
            if (++s == NSLOT) { s = 0; ph ^= 1; }
        }
        if (tid == 0) TS(3);
    } else if (warp == 8) {
        uint32_t nxt = 0;
        {
            if (lane >= 2 && lane < NSLOT) mbar_init(bar_full + lane * 8, 1);
            if (lane < NSLOT) {
                mbar_init(bar_aux + lane * 8, 1);
                mbar_init(bar_empty + lane * 8, 8);
                mbar_init(bar_desc + lane * 8, 1);
            }
            if (lane == 31) mbar_init(sb + S_PBAR + 8, 8);
            asm volatile("fence.mbarrier_init.release.cluster;" ::: "memory");
            __syncwarp();
        }
        if (lane == 0) {
            mbar_arrive(bar_desc);
            mbar_arrive(bar_desc + 8);
        }
        __syncthreads();
        if (lane == 0) {
            TS(7);
            const uint64_t pol = policy_evict_first();
            uint32_t base = 0;
            int tk = 2 / SUP;
            int s = 2, sw = 0, it = 2;
            uint32_t ph = 1, phw = 0;
#pragma unroll 1
            while (true) {
                uint32_t d0 = 0;
#pragma unroll 1
                for (int hf = 0; hf < SUP; hf++) {
                    if (hf == 1 && (d0 & D_FINE)) break;
                    if (it == NSLOT - 1) mbar_wait(sb + S_PBAR + 8, 0);
                    mbar_wait(bar_empty + s * 8, ph);
                    if (it >= WINF) {
                        mbar_wait(bar_full + sw * 8, phw);
                        if (++sw == NSLOT) { sw = 0; phw ^= 1; }
                    }
                    if (hf == 0) {
                        int cur = sc + tk * P.nstream;
                        if (tk >= NSTATIC) {
                            if (tk == NSTATIC)
                                base = (get_epoch(sb) - 1) * (uint32_t)(TOTAL_TICKETS - (NSTATIC - 1) * P.nstream) - (uint32_t)(NSTATIC * P.nstream);
                            cur = (int)(nxt - base);
                            if (cur >= TOTAL_TICKETS) goto producer_done;
                        }
                        d0 = decode_ticket(cur);
                        tk++;
                    }
                    const uint32_t d = d0 + hf;
                    sts32(sb + S_DESC + s * 4, d);
                    mbar_expect_tx(bar_full + s * 8, ITEM_BYTES);
                    bulk_load(sb + S_RING + s * ITEM_BYTES, ((d >> 31) ? P.v : P.k) + ((size_t)((d >> 8) & 0xFFu) * SK + (d & 0xFFu) * ITEM_KEYS) * DH,
                              ITEM_BYTES, bar_full + s * 8, pol);
                    mbar_arrive(bar_desc + s * 8);
                    if ((hf == SUP - 1 || (d0 & D_FINE)) && tk >= NSTATIC) nxt = atomicAdd(&g_ticket, 1u);
                    if (++s == NSLOT) { s = 0; ph ^= 1; }
                    it++;
                }
            }
        producer_done:
#pragma unroll 1
            for (int k = 0; k < NSLOT; k++) {
                if (k > 0) mbar_wait(bar_empty + s * 8, ph);
                sts32(sb + S_DESC + s * 4, STOPD);
                mbar_arrive(bar_desc + s * 8);
                if (k == 0) mbar_arrive(bar_full + s * 8);
                if (++s == NSLOT) { s = 0; ph ^= 1; }
            }
        }
    } else if (warp >= 9 + NSLOT) {
        __syncthreads();
    } else {
        __syncthreads();
        publish_epoch();
        const int s = warp - 9;
        const uint32_t epoch = get_epoch(sb);
        const uint32_t tag16 = epoch & 0xFFFFu, tag2 = epoch & 3u;
        const uint32_t qp = sb + S_QP + s * 256;
        const uint32_t red = sb + S_RED + s * 4096;
        uint32_t ph = 0;
#pragma unroll 1
        while (true) {
            mbar_wait(bar_desc + s * 8, ph);
            const uint32_t desc = lds32(sb + S_DESC + s * 4);
            if (desc == STOPD) break;
            const int is_v = desc >> 31, mp = (desc >> 8) & 0xFF, ch = desc & 0xFF;
            if (!is_v) {
                const uint32_t* src = g_q + mp * DH + lane * 4;
                uint4 w = ldx128(src);
                Spin sp;
                while (__any_sync(0xffffffffu, ((w.x & 0xFFFFu) != tag16) | ((w.y & 0xFFFFu) != tag16) | ((w.z & 0xFFFFu) != tag16) | ((w.w & 0xFFFFu) != tag16))) {
                    sp.tick(100);
                    w = ldx128(src);
                }
                sts64(qp + lane * 8, (w.x >> 16) | (w.y & 0xFFFF0000u), (w.z >> 16) | (w.w & 0xFFFF0000u));
            } else {
                const uint32_t* src = g_sc + (size_t)mp * SK + ch * ITEM_KEYS + lane * 4;
                const unsigned long long* ssrc = g_st + mp * IPP + lane;
                uint4 w = ldx128(src);
                unsigned long long st = ldx64(ssrc);
                Spin sp;
                while (__any_sync(0xffffffffu, ((w.x & 0xFFFFu) != tag16) | ((w.y & 0xFFFFu) != tag16) | ((w.z & 0xFFFFu) != tag16) |
                                                   ((w.w & 0xFFFFu) != tag16) | (((uint32_t)(st >> 32) & 0xFFFFu) != tag16))) {
                    sp.tick(100);
                    w = ldx128(src);
                    st = ldx64(ssrc);
                }
                const float mi = bfhi((uint32_t)(st >> 32)), li = __uint_as_float((uint32_t)st);
                const float m = warp_max(mi);
                const float sum = warp_sum(li * expf(mi - m));
                const float p0 = expf(bfhi(w.x) - m) / sum, p1 = expf(bfhi(w.y) - m) / sum;
                const float p2 = expf(bfhi(w.z) - m) / sum, p3 = expf(bfhi(w.w) - m) / sum;
                sts64(qp + lane * 8, pack2(p0, p1), pack2(p2, p3));
            }
            __syncwarp();
            if (lane == 0) mbar_arrive(bar_aux + s * 8);
            mbar_wait(bar_empty + s * 8, ph);
            if (!is_v) {
                uint4 w = lds128(red + lane * 16);
                const float s0 = __uint_as_float(w.x), s1 = __uint_as_float(w.y), s2 = __uint_as_float(w.z), s3 = __uint_as_float(w.w);
                const float m = warp_max(fmaxf(fmaxf(s0, s1), fmaxf(s2, s3)));
                const float ms = (m == -INFINITY) ? 0.f : m;
                const float l = warp_sum((expf(s0 - ms) + expf(s1 - ms)) + (expf(s2 - ms) + expf(s3 - ms)));
                stx128(g_sc + (size_t)mp * SK + ch * ITEM_KEYS + lane * 4, w.x | tag16, w.y | tag16, w.z | tag16, w.w | tag16);
                if (lane == 0)
                    stx64(g_st + mp * IPP + ch, ((unsigned long long)((__float_as_uint(m) & 0xFFFF0000u) | tag16) << 32) | __float_as_uint(l));
            } else if (desc & (D_FINE | 1u)) {
                float a0 = 0.f, a1 = 0.f, a2 = 0.f, a3 = 0.f;
#pragma unroll
                for (int w8 = 0; w8 < 8; w8++) {
                    uint4 w = lds128(red + w8 * 512 + lane * 16);
                    a0 += __uint_as_float(w.x); a1 += __uint_as_float(w.y); a2 += __uint_as_float(w.z); a3 += __uint_as_float(w.w);
                }
                stx128(g_op + ((size_t)mp * IPP + ((desc & D_FINE) ? ch : ch >> 1)) * DH + lane * 4, (__float_as_uint(a0) & ~3u) | tag2, (__float_as_uint(a1) & ~3u) | tag2,
                       (__float_as_uint(a2) & ~3u) | tag2, (__float_as_uint(a3) & ~3u) | tag2);
            }
            ph ^= 1;
        }
    }
}

}

typedef CUresult (*EncodeTiledFn)(CUtensorMap*, CUtensorMapDataType, cuuint32_t, void*, const cuuint64_t*, const cuuint64_t*,
                                  const cuuint32_t*, const cuuint32_t*, CUtensorMapInterleave, CUtensorMapSwizzle,
                                  CUtensorMapL2promotion, CUtensorMapFloatOOBfill);

static void make_map(EncodeTiledFn enc, CUtensorMap* tm, const void* base, int rows, int cols, int box_cols, int box_rows, CUtensorMapSwizzle sw) {
    cuuint64_t dims[2] = {(cuuint64_t)cols, (cuuint64_t)rows};
    cuuint64_t strides[1] = {(cuuint64_t)cols * 2};
    cuuint32_t box[2] = {(cuuint32_t)box_cols, (cuuint32_t)box_rows};
    cuuint32_t estr[2] = {1, 1};
    enc(tm, CU_TENSOR_MAP_DATA_TYPE_BFLOAT16, 2, const_cast<void*>(base), dims, strides, box, estr, CU_TENSOR_MAP_INTERLEAVE_NONE, sw,
        CU_TENSOR_MAP_L2_PROMOTION_NONE, CU_TENSOR_MAP_FLOAT_OOB_FILL_NONE);
}

extern "C" void kernel_launch(void* const* d_in, const int* in_sizes, int n_in, void* d_out, int out_size) {
    (void)in_sizes; (void)n_in; (void)out_size;
    static int nsm = 0;
    static EncodeTiledFn enc = nullptr;
    if (nsm == 0) {
        int dev = 0;
        cudaGetDevice(&dev);
        cudaDeviceGetAttribute(&nsm, cudaDevAttrMultiProcessorCount, dev);
        cudaFuncSetAttribute(fused_decode_kernel, cudaFuncAttributeMaxDynamicSharedMemorySize, SMEM_BYTES);
        void* fn = nullptr;
        cudaDriverEntryPointQueryResult qr;
        cudaGetDriverEntryPoint("cuTensorMapEncodeTiled", &fn, cudaEnableDefault, &qr);
        enc = (EncodeTiledFn)fn;
    }
    Params P;
    make_map(enc, &P.tm_wqs, d_in[3], DM, NH * DH, 16, 256, CU_TENSOR_MAP_SWIZZLE_NONE);
    make_map(enc, &P.tm_wq, d_in[3], DM, NH * DH, 64, 128, CU_TENSOR_MAP_SWIZZLE_128B);
    make_map(enc, &P.tm_wo, d_in[4], NH * DH, DM, 64, 128, CU_TENSOR_MAP_SWIZZLE_128B);
    make_map(enc, &P.tm_w1, d_in[6], DM, FF, 64, 128, CU_TENSOR_MAP_SWIZZLE_128B);
    make_map(enc, &P.tm_w2, d_in[8], FF, DM, 64, 128, CU_TENSOR_MAP_SWIZZLE_128B);
    P.x = (const __nv_bfloat16*)d_in[0];
    P.k = (const __nv_bfloat16*)d_in[1];
    P.v = (const __nv_bfloat16*)d_in[2];
    P.b1 = (const __nv_bfloat16*)d_in[7];
    P.b2 = (const __nv_bfloat16*)d_in[9];
    P.out = (__nv_bfloat16*)d_out;
    int grid = nsm < MAX_CTAS ? nsm : MAX_CTAS;
    P.nstream = grid - NSPEC;
    fused_decode_kernel<<<grid, NTHREADS, SMEM_BYTES, cudaStreamPerThread>>>(P);
}
```

```cpp
#include <cuda_runtime.h>
#include <cuda.h>
#include <cuda_bf16.h>
#include <stdint.h>

namespace {

constexpr int NB = 8, NH = 32, SK = 4096, DH = 128, DM = 512, FF = 1792;
constexpr int NPAIR = NB * NH;

#define CFG_NSLOT 6
#define CFG_LAG 32
#define CFG_NU 4
#define CFG_W 2
#define CFG_TR 1
#define CFG_SLEEP 1000
#define CFG_SLEEP_LAST 100
#define CFG_FINE 8
#define CFG_QH 4
constexpr int HG = 4;
constexpr int LAG = CFG_LAG;
constexpr int NSLOT = CFG_NSLOT;
constexpr int NU = CFG_NU;
constexpr int NSPEC = 4 * NU;
constexpr int ITEM_KEYS = 128;
constexpr int ITEM_BYTES = ITEM_KEYS * DH * 2;
constexpr int IPP = SK / ITEM_KEYS;
constexpr int SUP = 2;
constexpr int PPP = IPP / SUP;
constexpr int FINEP = CFG_FINE;
constexpr int TOTAL_TICKETS = NPAIR * (IPP + PPP) + FINEP * (IPP - PPP);
constexpr int NSTATIC = CFG_NSLOT;
constexpr int WINF = CFG_W;
constexpr int TR_GROUPS = CFG_TR;
constexpr int QH_STREAM = CFG_QH;
constexpr int NPOLL = 8;
constexpr int NWARPS = (9 + NSLOT > 8 + NPOLL) ? 9 + NSLOT : 8 + NPOLL;
constexpr int NTHREADS = NWARPS * 32;
constexpr int MAX_CTAS = 256;

constexpr int XN_PITCH = 1040;
constexpr int S_RING = 0;
constexpr int S_QP = S_RING + NSLOT * ITEM_BYTES;
constexpr int S_RED = S_QP + NSLOT * 256;
constexpr int PRO_BYTES = 8 * XN_PITCH + 8 * 8 * 20 * 4;
constexpr int RED_BYTES = (NSLOT * 4096 > PRO_BYTES) ? NSLOT * 4096 : PRO_BYTES;
constexpr int S_BAR = S_RED + RED_BYTES;
constexpr int S_PBAR = S_BAR + 4 * NSLOT * 8;
constexpr int S_DESC = S_PBAR + 16;
constexpr int STREAM_SMEM = S_DESC + NSLOT * 4 + 32;

constexpr int CH_BYTES = 128 * 128 * 2;
constexpr int NBUF = 5;
constexpr int H_PITCH = FF * 2 + 16;
constexpr int P_RING = 0;
constexpr int P_XN = P_RING + NBUF * CH_BYTES;
constexpr int P_H = P_XN + 8 * XN_PITCH;
constexpr int P_O = P_H + 8 * H_PITCH;
constexpr int P_ZERO = P_O + 16 * 256;
constexpr int P_TMP = P_ZERO + 256;
constexpr int P_BAR = P_TMP + 4 * 512;
constexpr int P_GATE = P_BAR + (NBUF + HG + 36) * 8;
constexpr int P_END = P_GATE + 8;
constexpr int SMEM_BYTES = (((STREAM_SMEM > P_END + 16) ? STREAM_SMEM : P_END + 16) + 15) / 16 * 16;
constexpr int EPOCH_OFF = SMEM_BYTES - 16;
static_assert(SMEM_BYTES <= 232448, "smem");
static_assert(SMEM_BYTES % 16 == 0, "ring");
static_assert(NSLOT >= 4 && WINF >= 2 && WINF <= NSLOT, "ring");
static_assert(S_DESC + NSLOT * 4 <= EPOCH_OFF && P_END <= EPOCH_OFF, "smem");

constexpr long long SPIN_LIMIT = 2000000000LL;

__device__ unsigned int g_epoch[MAX_CTAS];
__device__ unsigned int g_ticket;
__device__ __align__(128) uint32_t g_q[NPAIR * DH];
__device__ __align__(128) uint32_t g_sc[NPAIR * SK];
__device__ __align__(128) unsigned long long g_st[NPAIR * IPP];
__device__ __align__(128) uint32_t g_op[NPAIR * IPP * DH];
__device__ __align__(128) uint32_t g_h[NB * FF];

__device__ __forceinline__ uint32_t smem_u32(const void* p) { return (uint32_t)__cvta_generic_to_shared(p); }
__device__ __forceinline__ float bf16r(float x) { return __bfloat162float(__float2bfloat16_rn(x)); }
__device__ __forceinline__ float bflo(uint32_t w) { return __uint_as_float(w << 16); }
__device__ __forceinline__ float bfhi(uint32_t w) { return __uint_as_float(w & 0xFFFF0000u); }
__device__ __forceinline__ uint32_t pack2(float lo, float hi) {
    uint32_t r;
    asm("cvt.rn.bf16x2.f32 %0, %1, %2;" : "=r"(r) : "f"(hi), "f"(lo));
    return r;
}
__device__ __forceinline__ void mbar_init(uint32_t bar, int cnt) {
    asm volatile("mbarrier.init.shared::cta.b64 [%0], %1;" ::"r"(bar), "r"(cnt) : "memory");
}
__device__ __forceinline__ void mbar_expect_tx(uint32_t bar, uint32_t bytes) {
    asm volatile("mbarrier.arrive.expect_tx.shared::cta.b64 _, [%0], %1;" ::"r"(bar), "r"(bytes) : "memory");
}
__device__ __forceinline__ void mbar_arrive(uint32_t bar) {
    asm volatile("mbarrier.arrive.shared::cta.b64 _, [%0];" ::"r"(bar) : "memory");
}
__device__ __forceinline__ bool mbar_try(uint32_t bar, uint32_t parity) {
    uint32_t ok;
    asm volatile(
        "{\n.reg .pred p;\nmbarrier.try_wait.parity.shared::cta.b64 p, [%1], %2;\nselp.u32 %0, 1, 0, p;\n}"
        : "=r"(ok) : "r"(bar), "r"(parity) : "memory");
    return ok != 0;
}
__device__ __forceinline__ void mbar_wait(uint32_t bar, uint32_t parity) {
    if (mbar_try(bar, parity)) return;
    long long t0 = clock64();
    while (!mbar_try(bar, parity)) {
        if (clock64() - t0 > SPIN_LIMIT) __trap();
    }
}
__device__ __forceinline__ void bulk_load(uint32_t dst, const void* src, uint32_t bytes, uint32_t bar, uint64_t pol) {
    asm volatile(
        "cp.async.bulk.shared::cluster.global.mbarrier::complete_tx::bytes.L2::cache_hint [%0], [%1], %2, [%3], %4;"
        ::"r"(dst), "l"(src), "r"(bytes), "r"(bar), "l"(pol) : "memory");
}
__device__ __forceinline__ void bar_sync256() { asm volatile("bar.sync 1, 256;" ::: "memory"); }

__device__ __forceinline__ uint4 lds128(uint32_t a) {
    uint4 v;
    asm volatile("ld.shared.v4.u32 {%0,%1,%2,%3}, [%4];" : "=r"(v.x), "=r"(v.y), "=r"(v.z), "=r"(v.w) : "r"(a));
    return v;
}
__device__ __forceinline__ uint2 lds64(uint32_t a) {
    uint2 v;
    asm volatile("ld.shared.v2.u32 {%0,%1}, [%2];" : "=r"(v.x), "=r"(v.y) : "r"(a));
    return v;
}
__device__ __forceinline__ uint32_t lds32(uint32_t a) {
    uint32_t v;
    asm volatile("ld.shared.u32 %0, [%1];" : "=r"(v) : "r"(a));
    return v;
}
__device__ __forceinline__ uint32_t lds32_volatile(uint32_t a) {
    uint32_t v;
    asm volatile("ld.volatile.shared.u32 %0, [%1];" : "=r"(v) : "r"(a) : "memory");
    return v;
}
__device__ __forceinline__ void sts128(uint32_t a, uint32_t x, uint32_t y, uint32_t z, uint32_t w) {
    asm volatile("st.shared.v4.u32 [%0], {%1,%2,%3,%4};" ::"r"(a), "r"(x), "r"(y), "r"(z), "r"(w) : "memory");
}
__device__ __forceinline__ void sts64(uint32_t a, uint32_t x, uint32_t y) {
    asm volatile("st.shared.v2.u32 [%0], {%1,%2};" ::"r"(a), "r"(x), "r"(y) : "memory");
}
__device__ __forceinline__ void sts32(uint32_t a, uint32_t x) {
    asm volatile("st.shared.u32 [%0], %1;" ::"r"(a), "r"(x) : "memory");
}
__device__ __forceinline__ void sts16(uint32_t a, uint32_t x) {
    asm volatile("st.shared.u16 [%0], %1;" ::"r"(a), "h"((unsigned short)x) : "memory");
}
__device__ __forceinline__ void ldsm4t(uint32_t a, uint32_t& r0, uint32_t& r1, uint32_t& r2, uint32_t& r3) {
    asm volatile("ldmatrix.sync.aligned.m8n8.x4.trans.shared.b16 {%0,%1,%2,%3}, [%4];"
                 : "=r"(r0), "=r"(r1), "=r"(r2), "=r"(r3) : "r"(a));
}
__device__ __forceinline__ void ldsm4(uint32_t a, uint32_t& r0, uint32_t& r1, uint32_t& r2, uint32_t& r3) {
    asm volatile("ldmatrix.sync.aligned.m8n8.x4.shared.b16 {%0,%1,%2,%3}, [%4];"
                 : "=r"(r0), "=r"(r1), "=r"(r2), "=r"(r3) : "r"(a));
}
__device__ __forceinline__ void mma16816(float* c, uint32_t a0, uint32_t a1, uint32_t a2, uint32_t a3, uint32_t b0, uint32_t b1) {
    asm volatile(
        "mma.sync.aligned.m16n8k16.row.col.f32.bf16.bf16.f32 {%0,%1,%2,%3}, {%4,%5,%6,%7}, {%8,%9}, {%0,%1,%2,%3};"
        : "+f"(c[0]), "+f"(c[1]), "+f"(c[2]), "+f"(c[3])
        : "r"(a0), "r"(a1), "r"(a2), "r"(a3), "r"(b0), "r"(b1));
}
__device__ __forceinline__ uint4 ldx128(const void* p) {
    uint4 v;
    asm volatile("ld.relaxed.gpu.global.v4.u32 {%0,%1,%2,%3}, [%4];" : "=r"(v.x), "=r"(v.y), "=r"(v.z), "=r"(v.w) : "l"(p) : "memory");
    return v;
}
__device__ __forceinline__ uint32_t ldx32(const void* p) {
    uint32_t v;
    asm volatile("ld.relaxed.gpu.global.u32 %0, [%1];" : "=r"(v) : "l"(p) : "memory");
    return v;
}
__device__ __forceinline__ unsigned ld_epoch(const unsigned* p) {
    unsigned v;
    asm volatile("ld.global.u32 %0, [%1];" : "=r"(v) : "l"(p));
    return v;
}
__device__ __forceinline__ unsigned long long ldx64(const void* p) {
    unsigned long long v;
    asm volatile("ld.relaxed.gpu.global.u64 %0, [%1];" : "=l"(v) : "l"(p) : "memory");
    return v;
}
__device__ __forceinline__ void stx128(void* p, uint32_t x, uint32_t y, uint32_t z, uint32_t w) {
    asm volatile("st.relaxed.gpu.global.v4.u32 [%0], {%1,%2,%3,%4};" ::"l"(p), "r"(x), "r"(y), "r"(z), "r"(w) : "memory");
}
__device__ __forceinline__ void stx64(void* p, unsigned long long v) {
    asm volatile("st.relaxed.gpu.global.u64 [%0], %1;" ::"l"(p), "l"(v) : "memory");
}
__device__ __forceinline__ void stx32(void* p, uint32_t v) {
    asm volatile("st.relaxed.gpu.global.u32 [%0], %1;" ::"l"(p), "r"(v) : "memory");
}
__device__ __forceinline__ uint4 ldg128(const void* p) {
    uint4 v;
    asm volatile("ld.global.nc.L1::no_allocate.v4.u32 {%0,%1,%2,%3}, [%4];" : "=r"(v.x), "=r"(v.y), "=r"(v.z), "=r"(v.w) : "l"(p));
    return v;
}
__device__ __forceinline__ float ldg_bf16(const __nv_bfloat16* p) { return __bfloat162float(__ldg(p)); }

__device__ __forceinline__ float warp_max(float v) {
#pragma unroll
    for (int o = 16; o > 0; o >>= 1) v = fmaxf(v, __shfl_xor_sync(0xffffffffu, v, o));
    return v;
}
__device__ __forceinline__ float warp_sum(float v) {
#pragma unroll
    for (int o = 16; o > 0; o >>= 1) v += __shfl_xor_sync(0xffffffffu, v, o);
    return v;
}
struct Spin {
    long long t0;
    __device__ __forceinline__ Spin() : t0(0) {}
    __device__ __forceinline__ void tick(unsigned ns) {
        if (t0 == 0) t0 = clock64();
        else if (clock64() - t0 > SPIN_LIMIT) __trap();
        if (ns) __nanosleep(ns);
    }
};

__device__ __forceinline__ uint32_t get_epoch(uint32_t sb) {
    mbar_wait(sb + EPOCH_OFF + 8, 0);
    return lds32(sb + EPOCH_OFF);
}
struct Params {
    CUtensorMap tm_wqs, tm_wq, tm_w1, tm_w2, tm_wo;
    const __nv_bfloat16 *x, *k, *v, *b1, *b2;
    __nv_bfloat16* out;
    int nstream;
};
__device__ __forceinline__ uint64_t policy_evict_first() {
    uint64_t pol;
    asm volatile("createpolicy.fractional.L2::evict_first.b64 %0, 1.0;" : "=l"(pol));
    return pol;
}
__device__ __forceinline__ uint64_t policy_evict_normal() {
    uint64_t pol;
    asm volatile("createpolicy.fractional.L2::evict_normal.b64 %0, 1.0;" : "=l"(pol));
    return pol;
}
__device__ __forceinline__ void tma_2d(uint32_t dst, const CUtensorMap* tm, int x, int y, uint32_t bar, uint64_t pol) {
    asm volatile("cp.async.bulk.tensor.2d.shared::cluster.global.tile.mbarrier::complete_tx::bytes.L2::cache_hint [%0], [%1, {%2, %3}], [%4], %5;"
                 ::"r"(dst), "l"(tm), "r"(x), "r"(y), "r"(bar), "l"(pol) : "memory");
}
__device__ __forceinline__ void chunk_tma(uint32_t dst, const CUtensorMap* tm, int col, int row, uint32_t bar, bool shared_by_many) {
    const uint64_t pol = shared_by_many ? policy_evict_normal() : policy_evict_first();
    mbar_expect_tx(bar, CH_BYTES);
    tma_2d(dst, tm, col, row, bar, pol);
    tma_2d(dst + CH_BYTES / 2, tm, col + 64, row, bar, pol);
}

constexpr uint32_t D_V = 1u << 31, D_FINE = 1u << 30;
__device__ __forceinline__ uint32_t decode_ticket(int idx) {
    constexpr int A = LAG * IPP;
    constexpr int MID = (NPAIR - LAG) * (IPP + PPP);
    constexpr int C = (LAG - FINEP) * PPP;
    int p, ch;
    uint32_t flags;
    if (idx < A) {
        flags = D_FINE; p = idx / IPP; ch = idx % IPP;
    } else if (idx < A + MID) {
        const int j = idx - A, t = j / 3, r3 = j % 3;
        p = t / PPP;
        ch = (t % PPP) * SUP;
        if (r3 == 1) flags = D_V;
        else { flags = D_FINE; p += LAG; ch += r3 >> 1; }
    } else if (idx < A + MID + C) {
        int j = idx - A - MID;
        flags = D_V; p = NPAIR - LAG + j / PPP; ch = (j % PPP) * SUP;
    } else {
        int j = idx - A - MID - C;
        flags = D_V | D_FINE; p = NPAIR - FINEP + j / IPP; ch = j % IPP;
    }
    const int grp = p / (8 * HG), r = p % (8 * HG);
    const bool tr = grp >= NH / HG - TR_GROUPS;
    const int b = tr ? r % 8 : r / HG, h = grp * HG + (tr ? r / 8 : r % HG);
    return flags | ((uint32_t)(b * NH + h) << 8) | (uint32_t)ch;
}
constexpr uint32_t STOPD = 0x7FFFFFFFu;

__device__ __forceinline__ void layernorm_row(uint4 xa, uint4 xb, uint32_t dst_row, int lane) {
    float v[16];
    v[0] = bflo(xa.x); v[1] = bfhi(xa.x); v[2] = bflo(xa.y); v[3] = bfhi(xa.y);
    v[4] = bflo(xa.z); v[5] = bfhi(xa.z); v[6] = bflo(xa.w); v[7] = bfhi(xa.w);
    v[8] = bflo(xb.x); v[9] = bfhi(xb.x); v[10] = bflo(xb.y); v[11] = bfhi(xb.y);
    v[12] = bflo(xb.z); v[13] = bfhi(xb.z); v[14] = bflo(xb.w); v[15] = bfhi(xb.w);
    float s = 0.f;
#pragma unroll
    for (int i = 0; i < 16; i++) s += v[i];
    s = warp_sum(s);
    const float mean = s * (1.0f / DM);
    float q = 0.f;
#pragma unroll
    for (int i = 0; i < 16; i++) { float d = v[i] - mean; q += d * d; }
    q = warp_sum(q);
    const float m = bf16r(mean);
    const float var = bf16r(q * (1.0f / DM));
    const float den = bf16r(sqrtf(bf16r(var + 1e-5f)));
    uint32_t o[8];
#pragma unroll
    for (int i = 0; i < 8; i++) {
        float a = bf16r(v[2 * i] - m) / den;
        float b = bf16r(v[2 * i + 1] - m) / den;
        o[i] = pack2(a, b);
    }
    sts128(dst_row + lane * 16, o[0], o[1], o[2], o[3]);
    sts128(dst_row + 512 + lane * 16, o[4], o[5], o[6], o[7]);
}

__device__ __forceinline__ void chunk_load_a(uint32_t (&a)[8][4], uint32_t chunk, int warp, int lane) {
    const uint32_t a_addr = chunk + (warp >> 2) * (CH_BYTES / 2) + ((lane & 7) + ((lane >> 4) & 1) * 8) * 128 +
                            ((((warp & 3) * 2 + ((lane >> 3) & 1)) ^ (lane & 7)) << 4);
#pragma unroll
    for (int ks = 0; ks < 8; ks++) ldsm4t(a_addr + ks * 16 * 128, a[ks][0], a[ks][1], a[ks][2], a[ks][3]);
}
__device__ __forceinline__ void chunk_mma_b(float (&acc)[4][4], const uint32_t (&a)[8][4], uint32_t b_addr) {
    uint32_t bb[4][4];
#pragma unroll
    for (int q = 0; q < 4; q++) ldsm4(b_addr + q * 64, bb[q][0], bb[q][1], bb[q][2], bb[q][3]);
#pragma unroll
    for (int ks = 0; ks < 8; ks++)
        mma16816(acc[ks & 3], a[ks][0], a[ks][1], a[ks][2], a[ks][3], bb[ks >> 1][(ks & 1) * 2], bb[ks >> 1][(ks & 1) * 2 + 1]);
}
__device__ __forceinline__ void chunk_mma(float (&acc)[4][4], uint32_t chunk, uint32_t act, int act_pitch, int warp, int lane) {
    uint32_t a[8][4];
    chunk_load_a(a, chunk, warp, lane);
    chunk_mma_b(acc, a, act + (lane & 7) * act_pitch + (lane >> 3) * 16);
}
__device__ __forceinline__ float acc_sum(const float (&acc)[4][4], int e) { return (acc[0][e] + acc[1][e]) + (acc[2][e] + acc[3][e]); }
__device__ __forceinline__ void acc_zero(float (&acc)[4][4]) {
#pragma unroll
    for (int i = 0; i < 4; i++)
#pragma unroll
        for (int e = 0; e < 4; e++) acc[i][e] = 0.f;
}
__device__ __forceinline__ float gelu_tanh(float x) {
    const float kBeta = 0.7978845608028654f, kKappa = 0.044715f;
    float inner = kBeta * (x + kKappa * x * x * x);
    return 0.5f * x * (1.0f + tanhf(inner));
}

__device__ __forceinline__ void pair_seq(int n, int& grp, int& hl, int& bi) {
    constexpr int RPG = NB / NU;
    grp = n / (RPG * HG);
    const int q = n % (RPG * HG);
    const bool tr = grp >= NH / HG - TR_GROUPS;
    hl = tr ? q / RPG : q % HG;
    bi = tr ? q % RPG : q / HG;
}
constexpr int NSEQ = NPAIR / NU;
constexpr int NOB = NPOLL;
static_assert(TR_GROUPS == 1 && FINEP <= 8 * HG && FINEP <= LAG && PPP == 16, "pair order");
__device__ void special_cta(const Params& P, uint32_t sb, int sidx, int tid, uint4 xa, uint4 xb) {
    const int warp = tid >> 5, lane = tid & 31, g = lane >> 2, t = lane & 3;
    const int j = sidx & 3;
    const int u = sidx >> 2;

    const int nq = (NH - QH_STREAM - sidx + NSPEC - 1) / NSPEC;
    const int nslab = (FF / 128 - sidx + NSPEC - 1) / NSPEC;
    const int nq0 = nq > 0 ? 1 : 0;
    const int n1 = (nq + nslab) * 4, ntot = n1 + FF / 128;
    auto job_is_q = [&](int job) { return job < nq0 || job >= nq0 + nslab; };
    auto job_col = [&](int job) {
        return job_is_q(job) ? (QH_STREAM + sidx + (job < nq0 ? 0 : job - nslab) * NSPEC) * 128 : (sidx + (job - nq0) * NSPEC) * 128;
    };
    const uint32_t pbar = sb + P_BAR;
    auto issue = [&](int i) {
        if (i < ntot) {
            const uint32_t dst = sb + P_RING + (i % NBUF) * CH_BYTES, bar = pbar + (i % NBUF) * 8;
            if (i < n1) chunk_tma(dst, job_is_q(i >> 2) ? &P.tm_wq : &P.tm_w1, job_col(i >> 2), (i & 3) * 128, bar, false);
            else chunk_tma(dst, &P.tm_w2, j * 128, (i - n1) * 128, bar, true);
        }
    };
    if (tid == 0) {
#pragma unroll 1
        for (int i = 0; i < NBUF - 1; i++) issue(i);
    }
    uint32_t par = 0;
    layernorm_row(xa, xb, sb + P_XN + warp * XN_PITCH, lane);
    const uint32_t tag16 = get_epoch(sb) & 0xFFFFu;
    float acc[4][4];
    acc_zero(acc);
#pragma unroll 1
    for (int i = 0; i < ntot; i++) {
        if (i == n1) {
            Spin sp;
#pragma unroll 1
            for (int c0 = tid; c0 < NB * FF / 4; c0 += 256 * 7) {
                uint4 w[7];
#pragma unroll
                for (int q = 0; q < 7; q++) w[q] = ldx128(g_h + (c0 + q * 256) * 4);
#pragma unroll
                for (int q = 0; q < 7; q++) {
                    const int c = c0 + q * 256;
                    while (((w[q].x & 0xFFFFu) != tag16) | ((w[q].y & 0xFFFFu) != tag16) | ((w[q].z & 0xFFFFu) != tag16) | ((w[q].w & 0xFFFFu) != tag16)) {
                        sp.tick(100);
                        w[q] = ldx128(g_h + c * 4);
                    }
                    int b = c / (FF / 4), col = (c % (FF / 4)) * 4;
                    sts64(sb + P_H + b * H_PITCH + col * 2, (w[q].x >> 16) | (w[q].y & 0xFFFF0000u), (w[q].z >> 16) | (w[q].w & 0xFFFF0000u));
                }
            }
        }
        bar_sync256();
        if (tid == 0) issue(i + NBUF - 1);
        const int sl = i % NBUF;
        mbar_wait(pbar + sl * 8, (par >> sl) & 1u);
        par ^= 1u << sl;
        uint32_t chunk = sb + P_RING + sl * CH_BYTES;
        if (i < n1) {
            chunk_mma(acc, chunk, sb + P_XN + (i & 3) * 256, XN_PITCH, warp, lane);
            if ((i & 3) == 3) {
                if (job_is_q(i >> 2)) {
                    const int h = job_col(i >> 2) / 128;
#pragma unroll
                    for (int e = 0; e < 4; e++) {
                        int c = warp * 16 + g + (e >> 1) * 8, b = 2 * t + (e & 1);
                        stx32(g_q + (b * NH + h) * DH + c, (__float_as_uint(bf16r(acc_sum(acc, e))) & 0xFFFF0000u) | tag16);
                    }
                } else {
                    const int col = job_col(i >> 2) + warp * 16 + g;
#pragma unroll
                    for (int e = 0; e < 4; e++) {
                        int c = col + (e >> 1) * 8, b = 2 * t + (e & 1);
                        float hp = bf16r(acc_sum(acc, e));
                        float hb = bf16r(hp + ldg_bf16(P.b1 + c));
                        float gl = bf16r(gelu_tanh(hb));
                        stx32(g_h + b * FF + c, (__float_as_uint(gl) & 0xFFFF0000u) | tag16);
                    }
                }
                acc_zero(acc);
            }
        } else {
            chunk_mma(acc, chunk, sb + P_H + (i - n1) * 256, H_PITCH, warp, lane);
        }
    }
    const int col0 = j * 128 + warp * 16 + g;
    float ffn[4], xin[4];
#pragma unroll
    for (int e = 0; e < 4; e++) {
        int c = col0 + (e >> 1) * 8, b = 2 * t + (e & 1);
        ffn[e] = bf16r(bf16r(acc_sum(acc, e)) + ldg_bf16(P.b2 + c));
        xin[e] = ldg_bf16(P.x + b * DM + c);
    }
    acc_zero(acc);
    __nv_bfloat16* outp = P.out + col0;
    asm volatile("" : "+l"(outp));
    bar_sync256();
    if (tid == 0) {
#pragma unroll 1
        for (int c = 0; c < HG; c++) chunk_tma(sb + P_RING + c * CH_BYTES, &P.tm_wo, j * 128, c * 128, pbar + c * 8, true);
    }
    const uint32_t bar_cempty = pbar + NBUF * 8, bar_ofull = bar_cempty + HG * 8, bar_oempty = bar_ofull + 128;
    constexpr int RPG = NB / NU;
    uint32_t a[8][4];
    int a_head = -1;
#pragma unroll 1
    for (int n = 0; n < NPAIR / NU; n++) {
        int grp, hl, bi;
        pair_seq(n, grp, hl, bi);
        const int b = u + bi * NU;
        const int ob = (n % NOB) * 2 + ((n / NOB) & 1);
        if (grp * HG + hl != a_head) {
            if (bi == 0) mbar_wait(pbar + hl * 8, ((par >> hl) ^ grp) & 1u);
            chunk_load_a(a, sb + P_RING + hl * CH_BYTES, warp, lane);
            a_head = grp * HG + hl;
        }
        mbar_wait(bar_ofull + ob * 8, (n / (2 * NOB)) & 1);
        const uint32_t b_addr = ((lane & 7) == b ? sb + P_O + ob * 256 : sb + P_ZERO) + (lane >> 3) * 16;
        chunk_mma_b(acc, a, b_addr);
        __syncwarp();
        if (lane == 0) {
            mbar_arrive(bar_oempty + ob * 8);
            if (bi == RPG - 1 && grp + 1 < NH / HG) {
                mbar_arrive(bar_cempty + hl * 8);
                if (warp == hl) {
                    mbar_wait(bar_cempty + hl * 8, grp & 1);
                    chunk_tma(sb + P_RING + hl * CH_BYTES, &P.tm_wo, j * 128, ((grp + 1) * HG + hl) * 128, pbar + hl * 8, true);
                }
            }
        }
        __syncwarp();
    }
#pragma unroll
    for (int e = 0; e < 4; e++) {
        const int b = 2 * t + (e & 1);
        if (b % NU == u) {
            float a = bf16r(acc_sum(acc, e));
            float r = bf16r(bf16r(xin[e] + a) + ffn[e]);
            outp[b * DM + (e >> 1) * 8] = __float2bfloat16_rn(r);
        }
    }
}

__device__ __forceinline__ void fold16(const uint32_t* src, uint32_t tag2, unsigned sleep_ns, Spin& sp, float (&s)[4]) {
    constexpr int NV = 16;
    uint4 v[NV];
    uint32_t pending = 0;
#pragma unroll
    for (int i = 0; i < NV; i++) v[i] = ldx128(src + i * DH);
#pragma unroll
    for (int i = 0; i < NV; i++)
        if (((v[i].x ^ tag2) | (v[i].y ^ tag2) | (v[i].z ^ tag2) | (v[i].w ^ tag2)) & 3u) pending |= 1u << i;
    while (__any_sync(0xffffffffu, pending != 0)) {
        sp.tick(sleep_ns);
#pragma unroll
        for (int i = 0; i < NV; i++)
            if (pending & (1u << i)) v[i] = ldx128(src + i * DH);
#pragma unroll
        for (int i = 0; i < NV; i++)
            if ((((v[i].x ^ tag2) | (v[i].y ^ tag2) | (v[i].z ^ tag2) | (v[i].w ^ tag2)) & 3u) == 0) pending &= ~(1u << i);
    }
    s[0] = s[1] = s[2] = s[3] = 0.f;
#pragma unroll
    for (int i = 0; i < NV; i++) {
        s[0] += __uint_as_float(v[i].x & ~3u); s[1] += __uint_as_float(v[i].y & ~3u);
        s[2] += __uint_as_float(v[i].z & ~3u); s[3] += __uint_as_float(v[i].w & ~3u);
    }
}
__device__ __forceinline__ void wait_word(const uint32_t* p, uint32_t tag2, unsigned sleep_ns, Spin& sp) {
    uint32_t w = ldx32(p);
    while ((w ^ tag2) & 3u) {
        sp.tick(sleep_ns);
        w = ldx32(p);
    }
}
constexpr int NFINE = FINEP / NU;
static_assert(NFINE <= NPOLL / 2 && FINEP % 8 == 0, "fine pairs");

__device__ void special_poller(uint32_t sb, uint32_t epoch, int sidx, int pid, int lane) {
    const int u = sidx >> 2, g = lane >> 2, t = lane & 3;
    const uint32_t tag2 = epoch & 3u;
    const uint32_t pbar = sb + P_BAR;
    const uint32_t bar_ofull = pbar + (NBUF + HG) * 8, bar_oempty = bar_ofull + 128, bar_hfull = bar_oempty + 128;
#pragma unroll 1
    for (int n = pid; n < NSEQ + NOB; n += NOB) {
        const bool helper = n >= NSEQ;
        if (helper) {
            if (pid >= NFINE) break;
            n = NSEQ - NFINE + pid;
        }
        int grp, hl, bi;
        pair_seq(n, grp, hl, bi);
        const int b = u + bi * NU;
        const int ob = (n % NOB) * 2 + ((n / NOB) & 1);
        const uint32_t oph = (n / (2 * NOB)) & 1;
        const bool last = grp == NH / HG - 1;
        const uint32_t* src = g_op + ((size_t)(b * NH + grp * HG + hl) * IPP + (helper ? 16 : 0)) * DH + lane * 4;
        Spin sp;
        if (last) {
            while ((int)lds32_volatile(sb + P_GATE) < NSEQ - (NB / NU) * HG) sp.tick(64);
            wait_word(src - lane * 4, tag2, CFG_SLEEP_LAST, sp);
        } else {
            while ((int)lds32_volatile(sb + P_GATE) < n) sp.tick(64);
            wait_word(src - lane * 4 + (PPP - 1) * DH, tag2, CFG_SLEEP, sp);
            if (lane == 0) sts32(sb + P_GATE, (uint32_t)(n + 1));
        }
        float s[4];
        fold16(src, tag2, last ? 0 : CFG_SLEEP, sp, s);
        if (helper) {
            sts128(sb + P_TMP + pid * 512 + lane * 16, __float_as_uint(s[0]), __float_as_uint(s[1]), __float_as_uint(s[2]), __float_as_uint(s[3]));
            __syncwarp();
            if (lane == 0) mbar_arrive(bar_hfull + pid * 8);
            break;
        }
        if (n >= NSEQ - NFINE) {
            const int hp = n - (NSEQ - NFINE);
            mbar_wait(bar_hfull + hp * 8, 0);
            const uint4 o = lds128(sb + P_TMP + hp * 512 + lane * 16);
            s[0] += __uint_as_float(o.x); s[1] += __uint_as_float(o.y); s[2] += __uint_as_float(o.z); s[3] += __uint_as_float(o.w);
        }
        mbar_wait(bar_oempty + ob * 8, oph ^ 1);
        const uint32_t row = sb + P_O + ob * 256 + (16 * t + g) * 2;
        const uint32_t p01 = pack2(s[0], s[1]), p23 = pack2(s[2], s[3]);
        sts16(row, p01 & 0xFFFFu); sts16(row + 16, p01 >> 16);
        sts16(row + 128, p23 & 0xFFFFu); sts16(row + 144, p23 >> 16);
        __syncwarp();
        if (lane == 0) mbar_arrive(bar_ofull + ob * 8);
    }
}

__global__ void __launch_bounds__(NTHREADS, 1) fused_decode_kernel(const __grid_constant__ Params P) {
    extern __shared__ __align__(1024) unsigned char smem[];
    const uint32_t sb = smem_u32(smem);
    const int tid = threadIdx.x, warp = tid >> 5, lane = tid & 31;
    const int cta = blockIdx.x;
    const bool is_special = cta < NSPEC;
    const int sc = cta - NSPEC;
    const uint32_t bar_full = sb + S_BAR, bar_aux = bar_full + NSLOT * 8, bar_empty = bar_aux + NSLOT * 8, bar_desc = bar_empty + NSLOT * 8;

    if (tid == 256 && !is_special) {
        mbar_init(bar_full, 1);
        mbar_init(bar_full + 8, 1);
        mbar_init(sb + S_PBAR, 1);
        asm volatile("fence.mbarrier_init.release.cluster;" ::: "memory");
        if (sc < QH_STREAM * 8) {
            const uint32_t wst = sb + S_RING + (NSLOT - 1) * ITEM_BYTES;
            mbar_expect_tx(sb + S_PBAR, 16384);
            tma_2d(wst, &P.tm_wqs, sc * 16, 0, sb + S_PBAR, policy_evict_normal());
            tma_2d(wst + 8192, &P.tm_wqs, sc * 16, 256, sb + S_PBAR, policy_evict_normal());
        }
        static_assert(HG == 4 && IPP == 32 && LAG >= 8 * HG && LAG * IPP >= 2 * MAX_CTAS, "static first tickets");
        const uint64_t pol = policy_evict_first();
#pragma unroll
        for (int i = 0; i < 2; i++) {
            const int idx = sc + i * P.nstream;
            const uint32_t mp = (idx >> 7) * NH + ((idx >> 5) & 3), ch = idx & 31;
            mbar_expect_tx(bar_full + i * 8, ITEM_BYTES);
            bulk_load(sb + S_RING + i * ITEM_BYTES, P.k + ((size_t)mp * SK + ch * ITEM_KEYS) * DH, ITEM_BYTES, bar_full + i * 8, pol);
            sts32(sb + S_DESC + i * 4, D_FINE | (mp << 8) | ch);
        }
    }
    uint4 xa = make_uint4(0, 0, 0, 0), xb = xa;
    if (warp < 8 && (is_special || sc < QH_STREAM * 8)) {
        xa = ldg128(P.x + warp * DM + lane * 8);
        xb = ldg128(P.x + warp * DM + 256 + lane * 8);
    }
    unsigned e_prev = 0;
    if (tid == 288) {
        e_prev = ld_epoch(&g_epoch[cta]);
        mbar_init(sb + EPOCH_OFF + 8, 1);
        asm volatile("fence.mbarrier_init.release.cluster;" ::: "memory");
    }
    auto publish_epoch = [&]() {
        if (tid == 288) {
            g_epoch[cta] = e_prev + 1;
            sts32(sb + EPOCH_OFF, e_prev + 1);
            mbar_arrive(sb + EPOCH_OFF + 8);
        }
    };
    if (is_special) {
        if (tid == 0) {
            for (int i = 0; i < NBUF; i++) mbar_init(sb + P_BAR + i * 8, 1);
            for (int i = 0; i < HG; i++) mbar_init(sb + P_BAR + (NBUF + i) * 8, 8);
            for (int i = 0; i < 16; i++) mbar_init(sb + P_BAR + (NBUF + HG + i) * 8, 1);
            for (int i = 0; i < 16; i++) mbar_init(sb + P_BAR + (NBUF + HG + 16 + i) * 8, 8);
            for (int i = 0; i < 4; i++) mbar_init(sb + P_BAR + (NBUF + HG + 32 + i) * 8, 1);
            asm volatile("fence.mbarrier_init.release.cluster;" ::: "memory");
        }
        if (tid >= 32 && tid < 96) sts32(sb + P_ZERO + (tid - 32) * 4, 0u);
        if (tid == 96) sts32(sb + P_GATE, 0u);
        __syncthreads();
        publish_epoch();
        if (warp < 8) {
            special_cta(P, sb, cta, tid, xa, xb);
        } else if (warp < 8 + NPOLL) {
            special_poller(sb, get_epoch(sb), cta, warp - 8, lane);
        }
        return;
    }

    if (warp < 8) {
        const int g = lane >> 2, t = lane & 3;
        {
            const bool has_slice = sc < QH_STREAM * 8;
            __syncthreads();
            if (has_slice) {
                const uint32_t xn = sb + S_RED, rq = sb + S_RED + 8 * XN_PITCH;
                const uint32_t wst = sb + S_RING + (NSLOT - 1) * ITEM_BYTES;
                layernorm_row(xa, xb, xn + warp * XN_PITCH, lane);
                bar_sync256();
                uint32_t pph = 0;
#pragma unroll 1
                for (int slice = sc; slice < QH_STREAM * 8; slice += P.nstream, pph ^= 1) {
                    mbar_wait(sb + S_PBAR, pph);
                    float ca[4] = {0.f, 0.f, 0.f, 0.f};
#pragma unroll
                    for (int k2 = 0; k2 < 2; k2++) {
                        uint32_t b0, b1, b2, b3;
                        ldsm4(xn + (lane & 7) * XN_PITCH + (warp * 64 + k2 * 32 + (lane >> 3) * 8) * 2, b0, b1, b2, b3);
#pragma unroll
                        for (int k1 = 0; k1 < 2; k1++) {
                            uint32_t a0, a1, a2, a3;
                            ldsm4t(wst + (warp * 64 + k2 * 32 + k1 * 16 + (lane & 7) + ((lane >> 4) & 1) * 8) * 32 + ((lane >> 3) & 1) * 16, a0, a1, a2, a3);
                            mma16816(ca, a0, a1, a2, a3, k1 ? b2 : b0, k1 ? b3 : b1);
                        }
                    }
                    const uint32_t rb = rq + (warp * 8 * 20 + 2 * t * 20 + g) * 4;
                    sts32(rb, __float_as_uint(ca[0])); sts32(rb + 20 * 4, __float_as_uint(ca[1]));
                    sts32(rb + 32, __float_as_uint(ca[2])); sts32(rb + 20 * 4 + 32, __float_as_uint(ca[3]));
                    bar_sync256();
                    if (tid < 128) {
                        const int b = tid >> 4, col = tid & 15;
                        float s = 0.f;
#pragma unroll
                        for (int w = 0; w < 8; w++) s += __uint_as_float(lds32(rq + (w * 8 * 20 + b * 20 + col) * 4));
                        stx32(g_q + (b * NH + (slice >> 3)) * DH + (slice & 7) * 16 + col,
                              (__float_as_uint(bf16r(s)) & 0xFFFF0000u) | (get_epoch(sb) & 0xFFFFu));
                    }
                    bar_sync256();
                    if (tid == 0 && slice + P.nstream < QH_STREAM * 8) {
                        mbar_expect_tx(sb + S_PBAR, 16384);
                        tma_2d(wst, &P.tm_wqs, (slice + P.nstream) * 16, 0, sb + S_PBAR, policy_evict_normal());
                        tma_2d(wst + 8192, &P.tm_wqs, (slice + P.nstream) * 16, 256, sb + S_PBAR, policy_evict_normal());
                    }
                }
            }
            __syncwarp();
            if (lane == 0) mbar_arrive(sb + S_PBAR + 8);
        }
        uint32_t koff[4];
#pragma unroll
        for (int jj = 0; jj < 4; jj++) koff[jj] = (4 * (jj ^ (g & 1)) + t) * 16;
        const uint32_t krow = (warp * 16 + g) * 256;
        const int mj = lane >> 3, mr = lane & 7;
        const uint32_t vrow = (warp * 16 + 4 * (mr >> 1) + (mr & 1) + 2 * (mj >> 1)) * 256 + (mj & 1) * 128;
        uint32_t vmask[8];
#pragma unroll
        for (int i = 0; i < 8; i++) vmask[i] = (g == ((2 * t) ^ i) ? 0x0000FFFFu : 0u) | (g == ((2 * t + 1) ^ i) ? 0xFFFF0000u : 0u);
        const float scale = 0.08838834764831845f;

        int s = 0;
        uint32_t ph = 0;
        float o0[4] = {0.f, 0.f, 0.f, 0.f}, o1[4] = {0.f, 0.f, 0.f, 0.f};
#pragma unroll 1
        while (true) {
            mbar_wait(bar_full + s * 8, ph);
            const uint32_t desc = lds32(sb + S_DESC + s * 4);
            if (desc == STOPD) break;
            const uint32_t tile = sb + S_RING + s * ITEM_BYTES;
            const uint32_t qp = sb + S_QP + s * 256;
            const uint32_t red = sb + S_RED + s * 4096;
            mbar_wait(bar_aux + s * 8, ph);
            if (!(desc >> 31)) {
                float c0[4] = {0.f, 0.f, 0.f, 0.f}, c1[4] = {0.f, 0.f, 0.f, 0.f};
#pragma unroll
                for (int jj = 0; jj < 4; jj++) {
                    uint4 qf = lds128(qp + koff[jj]);
                    uint4 r = lds128(tile + krow + koff[jj]);
                    uint4 q8 = lds128(tile + krow + 2048 + koff[jj]);
                    mma16816(c0, r.x, q8.x, r.y, q8.y, qf.x, qf.y);
                    mma16816(c1, r.z, q8.z, r.w, q8.w, qf.z, qf.w);
                }
                float lo = (g & 1) ? c0[1] + c1[1] : c0[0] + c1[0];
                float hi = (g & 1) ? c0[3] + c1[3] : c0[2] + c1[2];
                float val = (t & 1) ? hi : lo;
                val = bf16r(bf16r(val) * scale);
                if (t < 2) sts32(red + (warp * 16 + g + 8 * t) * 4, __float_as_uint(val));
            } else {
                uint2 pp = lds64(qp + (warp * 16 + 4 * t) * 2);
#pragma unroll
                for (int i = 0; i < 8; i++) {
                    uint32_t a0, a1, a2, a3;
                    ldsm4t(tile + vrow + ((mr ^ i) << 4), a0, a1, a2, a3);
                    mma16816((i & 1) ? o1 : o0, a0, a1, a2, a3, pp.x & vmask[i], pp.y & vmask[i]);
                }
                if (desc & (D_FINE | 1u)) {
                    sts128(red + warp * 512 + lane * 16, __float_as_uint(o0[0] + o1[0]), __float_as_uint(o0[1] + o1[1]),
                           __float_as_uint(o0[2] + o1[2]), __float_as_uint(o0[3] + o1[3]));
#pragma unroll
                    for (int e = 0; e < 4; e++) { o0[e] = 0.f; o1[e] = 0.f; }
                }
            }
            __syncwarp();
            if (lane == 0) mbar_arrive(bar_empty + s * 8);
            if (++s == NSLOT) { s = 0; ph ^= 1; }
        }
    } else if (warp == 8) {
        uint32_t nxt = 0;
        {
            if (lane >= 2 && lane < NSLOT) mbar_init(bar_full + lane * 8, 1);
            if (lane < NSLOT) {
                mbar_init(bar_aux + lane * 8, 1);
                mbar_init(bar_empty + lane * 8, 8);
                mbar_init(bar_desc + lane * 8, 1);
            }
            if (lane == 31) mbar_init(sb + S_PBAR + 8, 8);
            asm volatile("fence.mbarrier_init.release.cluster;" ::: "memory");
            __syncwarp();
        }
        if (lane == 0) {
            mbar_arrive(bar_desc);
            mbar_arrive(bar_desc + 8);
        }
        __syncthreads();
        if (lane == 0) {
            const uint64_t pol = policy_evict_first();
            uint32_t base = 0;
            int tk = 2;
            int s = 2, sw = 0, it = 2;
            uint32_t ph = 1, phw = 0;
#pragma unroll 1
            while (true) {
                uint32_t d0 = 0;
#pragma unroll 1
                for (int hf = 0; hf < SUP; hf++) {
                    if (hf == 1 && (d0 & D_FINE)) break;
                    if (it == NSLOT - 1) mbar_wait(sb + S_PBAR + 8, 0);
                    mbar_wait(bar_empty + s * 8, ph);
                    if (it >= WINF) {
                        mbar_wait(bar_full + sw * 8, phw);
                        if (++sw == NSLOT) { sw = 0; phw ^= 1; }
                    }
                    if (hf == 0) {
                        int cur = sc + tk * P.nstream;
                        if (tk >= NSTATIC) {
                            if (tk == NSTATIC)
                                base = (get_epoch(sb) - 1) * (uint32_t)(TOTAL_TICKETS - (NSTATIC - 1) * P.nstream) - (uint32_t)(NSTATIC * P.nstream);
                            cur = (int)(nxt - base);
                            if (cur >= TOTAL_TICKETS) goto producer_done;
                        }
                        d0 = decode_ticket(cur);
                        tk++;
                    }
                    const uint32_t d = d0 + hf;
                    sts32(sb + S_DESC + s * 4, d);
                    mbar_expect_tx(bar_full + s * 8, ITEM_BYTES);
                    bulk_load(sb + S_RING + s * ITEM_BYTES, ((d >> 31) ? P.v : P.k) + ((size_t)((d >> 8) & 0xFFu) * SK + (d & 0xFFu) * ITEM_KEYS) * DH,
                              ITEM_BYTES, bar_full + s * 8, pol);
                    mbar_arrive(bar_desc + s * 8);
                    if ((hf == SUP - 1 || (d0 & D_FINE)) && tk >= NSTATIC) nxt = atomicAdd(&g_ticket, 1u);
                    if (++s == NSLOT) { s = 0; ph ^= 1; }
                    it++;
                }
            }
        producer_done:
#pragma unroll 1
            for (int k = 0; k < NSLOT; k++) {
                if (k > 0) mbar_wait(bar_empty + s * 8, ph);
                sts32(sb + S_DESC + s * 4, STOPD);
                mbar_arrive(bar_desc + s * 8);
                if (k == 0) mbar_arrive(bar_full + s * 8);
                if (++s == NSLOT) { s = 0; ph ^= 1; }
            }
        }
    } else if (warp >= 9 + NSLOT) {
        __syncthreads();
    } else {
        __syncthreads();
        publish_epoch();
        const int s = warp - 9;
        const uint32_t epoch = get_epoch(sb);
        const uint32_t tag16 = epoch & 0xFFFFu, tag2 = epoch & 3u;
        const uint32_t qp = sb + S_QP + s * 256;
        const uint32_t red = sb + S_RED + s * 4096;
        uint32_t ph = 0;
#pragma unroll 1
        while (true) {
            mbar_wait(bar_desc + s * 8, ph);
            const uint32_t desc = lds32(sb + S_DESC + s * 4);
            if (desc == STOPD) break;
            const int is_v = desc >> 31, mp = (desc >> 8) & 0xFF, ch = desc & 0xFF;
            if (!is_v) {
                const uint32_t* src = g_q + mp * DH + lane * 4;
                uint4 w = ldx128(src);
                Spin sp;
                while (__any_sync(0xffffffffu, ((w.x & 0xFFFFu) != tag16) | ((w.y & 0xFFFFu) != tag16) | ((w.z & 0xFFFFu) != tag16) | ((w.w & 0xFFFFu) != tag16))) {
                    sp.tick(100);
                    w = ldx128(src);
                }
                sts64(qp + lane * 8, (w.x >> 16) | (w.y & 0xFFFF0000u), (w.z >> 16) | (w.w & 0xFFFF0000u));
            } else {
                const uint32_t* src = g_sc + (size_t)mp * SK + ch * ITEM_KEYS + lane * 4;
                const unsigned long long* ssrc = g_st + mp * IPP + lane;
                uint4 w = ldx128(src);
                unsigned long long st = ldx64(ssrc);
                Spin sp;
                while (__any_sync(0xffffffffu, ((w.x & 0xFFFFu) != tag16) | ((w.y & 0xFFFFu) != tag16) | ((w.z & 0xFFFFu) != tag16) |
                                                   ((w.w & 0xFFFFu) != tag16) | (((uint32_t)(st >> 32) & 0xFFFFu) != tag16))) {
                    sp.tick(100);
                    w = ldx128(src);
                    st = ldx64(ssrc);
                }
                const float mi = bfhi((uint32_t)(st >> 32)), li = __uint_as_float((uint32_t)st);
                const float m = warp_max(mi);
                const float sum = warp_sum(li * expf(mi - m));
                const float p0 = expf(bfhi(w.x) - m) / sum, p1 = expf(bfhi(w.y) - m) / sum;
                const float p2 = expf(bfhi(w.z) - m) / sum, p3 = expf(bfhi(w.w) - m) / sum;
                sts64(qp + lane * 8, pack2(p0, p1), pack2(p2, p3));
            }
            __syncwarp();
            if (lane == 0) mbar_arrive(bar_aux + s * 8);
            mbar_wait(bar_empty + s * 8, ph);
            if (!is_v) {
                uint4 w = lds128(red + lane * 16);
                const float s0 = __uint_as_float(w.x), s1 = __uint_as_float(w.y), s2 = __uint_as_float(w.z), s3 = __uint_as_float(w.w);
                const float m = warp_max(fmaxf(fmaxf(s0, s1), fmaxf(s2, s3)));
                const float ms = (m == -INFINITY) ? 0.f : m;
                const float l = warp_sum((expf(s0 - ms) + expf(s1 - ms)) + (expf(s2 - ms) + expf(s3 - ms)));
                stx128(g_sc + (size_t)mp * SK + ch * ITEM_KEYS + lane * 4, w.x | tag16, w.y | tag16, w.z | tag16, w.w | tag16);
                if (lane == 0)
                    stx64(g_st + mp * IPP + ch, ((unsigned long long)((__float_as_uint(m) & 0xFFFF0000u) | tag16) << 32) | __float_as_uint(l));
            } else if (desc & (D_FINE | 1u)) {
                float a0 = 0.f, a1 = 0.f, a2 = 0.f, a3 = 0.f;
#pragma unroll
                for (int w8 = 0; w8 < 8; w8++) {
                    uint4 w = lds128(red + w8 * 512 + lane * 16);
                    a0 += __uint_as_float(w.x); a1 += __uint_as_float(w.y); a2 += __uint_as_float(w.z); a3 += __uint_as_float(w.w);
                }
                stx128(g_op + ((size_t)mp * IPP + ((desc & D_FINE) ? ch : ch >> 1)) * DH + lane * 4, (__float_as_uint(a0) & ~3u) | tag2, (__float_as_uint(a1) & ~3u) | tag2,
                       (__float_as_uint(a2) & ~3u) | tag2, (__float_as_uint(a3) & ~3u) | tag2);
            }
            ph ^= 1;
        }
    }
}

}

typedef CUresult (*EncodeTiledFn)(CUtensorMap*, CUtensorMapDataType, cuuint32_t, void*, const cuuint64_t*, const cuuint64_t*,
                                  const cuuint32_t*, const cuuint32_t*, CUtensorMapInterleave, CUtensorMapSwizzle,
                                  CUtensorMapL2promotion, CUtensorMapFloatOOBfill);

static void make_map(EncodeTiledFn enc, CUtensorMap* tm, const void* base, int rows, int cols, int box_cols, int box_rows, CUtensorMapSwizzle sw) {
    cuuint64_t dims[2] = {(cuuint64_t)cols, (cuuint64_t)rows};
    cuuint64_t strides[1] = {(cuuint64_t)cols * 2};
    cuuint32_t box[2] = {(cuuint32_t)box_cols, (cuuint32_t)box_rows};
    cuuint32_t estr[2] = {1, 1};
    enc(tm, CU_TENSOR_MAP_DATA_TYPE_BFLOAT16, 2, const_cast<void*>(base), dims, strides, box, estr, CU_TENSOR_MAP_INTERLEAVE_NONE, sw,
        CU_TENSOR_MAP_L2_PROMOTION_NONE, CU_TENSOR_MAP_FLOAT_OOB_FILL_NONE);
}

extern "C" void kernel_launch(void* const* d_in, const int* in_sizes, int n_in, void* d_out, int out_size) {
    (void)in_sizes; (void)n_in; (void)out_size;
    static int nsm = 0;
    static EncodeTiledFn enc = nullptr;
    if (nsm == 0) {
        int dev = 0;
        cudaGetDevice(&dev);
        cudaDeviceGetAttribute(&nsm, cudaDevAttrMultiProcessorCount, dev);
        cudaFuncSetAttribute(fused_decode_kernel, cudaFuncAttributeMaxDynamicSharedMemorySize, SMEM_BYTES);
        void* fn = nullptr;
        cudaDriverEntryPointQueryResult qr;
        cudaGetDriverEntryPoint("cuTensorMapEncodeTiled", &fn, cudaEnableDefault, &qr);
        enc = (EncodeTiledFn)fn;
    }
    Params P;
    make_map(enc, &P.tm_wqs, d_in[3], DM, NH * DH, 16, 256, CU_TENSOR_MAP_SWIZZLE_NONE);
    make_map(enc, &P.tm_wq, d_in[3], DM, NH * DH, 64, 128, CU_TENSOR_MAP_SWIZZLE_128B);
    make_map(enc, &P.tm_wo, d_in[4], NH * DH, DM, 64, 128, CU_TENSOR_MAP_SWIZZLE_128B);
    make_map(enc, &P.tm_w1, d_in[6], DM, FF, 64, 128, CU_TENSOR_MAP_SWIZZLE_128B);
    make_map(enc, &P.tm_w2, d_in[8], FF, DM, 64, 128, CU_TENSOR_MAP_SWIZZLE_128B);
    P.x = (const __nv_bfloat16*)d_in[0];
    P.k = (const __nv_bfloat16*)d_in[1];
    P.v = (const __nv_bfloat16*)d_in[2];
    P.b1 = (const __nv_bfloat16*)d_in[7];
    P.b2 = (const __nv_bfloat16*)d_in[9];
    P.out = (__nv_bfloat16*)d_out;
    int grid = nsm < MAX_CTAS ? nsm : MAX_CTAS;
    P.nstream = grid - NSPEC;
    fused_decode_kernel<<<grid, NTHREADS, SMEM_BYTES, cudaStreamPerThread>>>(P);
}
```
